```python
import torch

def _softmax(x, axis=-1):
    return torch.softmax(x, dim=axis)
def _gelu(x):
    return torch.nn.functional.gelu(x, approximate="tanh")
def _silu(x):
    return torch.nn.functional.silu(x)
def _sigmoid(x):
    return torch.sigmoid(x)
def _layernorm(x, axis=-1, eps=1e-5):
    m = x.mean(dim=axis, keepdim=True)
    v = x.var(dim=axis, keepdim=True, unbiased=False)
    return (x - m) / torch.sqrt(v + eps)
def _scatter_add(tgt, idx, src, axis=0):
    return tgt.clone().index_add_(axis, idx, src)
def _segment_sum(src, seg, n):
    out = torch.zeros((n,) + src.shape[1:], dtype=src.dtype)
    return out.index_add_(0, seg, src)
def _pad(x, pw):
    flat = tuple(v for pair in reversed(pw) for v in pair)
    return torch.nn.functional.pad(x, flat)

kernel_name = 'concat_heads__spectral_fnet__ssm_conv_h3__prompt'

def setup_inputs():

    _w = (lambda a: (lambda t: t.to(torch.bfloat16) if t.is_floating_point() else t)(torch.as_tensor(a)))
    def _A_setup():
        B, S, D = 1, 2048, 640
        ns = torch.arange(S)[:, None] * torch.arange(S)[None, :]
        nd = torch.arange(D)[:, None] * torch.arange(D)[None, :]
        Ws_re = torch.cos(-2.0 * torch.pi * ns / S).to(float)
        Ws_im = torch.sin(-2.0 * torch.pi * ns / S).to(float)
        Wd_re = torch.cos(-2.0 * torch.pi * nd / D).to(float)
        Wd_im = torch.sin(-2.0 * torch.pi * nd / D).to(float)
        return {
            "x": _w((lambda *s: torch.randn(*s, dtype=torch.bfloat16) * 0.05)(B, S, D)),
            "dft_seq_re": _w(Ws_re),
            "dft_seq_im": _w(Ws_im),
            "dft_hid_re": _w(Wd_re),
            "dft_hid_im": _w(Wd_im),
        }
    _A_in = _A_setup()

    def _B_setup():
        B, S, D = 1, 2048, 640
        ks = 4
        return {
            "q": _w((lambda *s: torch.randn(*s, dtype=torch.bfloat16) * 0.05)(B, S, D)),
            "k": _w((lambda *s: torch.randn(*s, dtype=torch.bfloat16) * 3.2)(B, S, D)),
            "v": _w((lambda *s: torch.randn(*s, dtype=torch.bfloat16) * 3.2)(B, S, D)),
            "shift_k": _w((lambda *s: torch.randn(*s, dtype=torch.bfloat16) * 3.2)(D, ks) * 0.5),
            "ssm_k": _w((lambda *s: torch.randn(*s, dtype=torch.bfloat16) * 3.2)(D, S) * (1.0 / S ** 0.5)),
            "ssm_D": _w((lambda *s: torch.randn(*s, dtype=torch.bfloat16) * 3.2)(D)),
        }
    _B_in = _B_setup()

    return {
        "A_x": _A_in["x"],
        "A_dft_seq_re": _A_in["dft_seq_re"],
        "A_dft_seq_im": _A_in["dft_seq_im"],
        "A_dft_hid_re": _A_in["dft_hid_re"],
        "A_dft_hid_im": _A_in["dft_hid_im"],
        "B_q": _B_in["q"],
        "B_k": _B_in["k"],
        "B_v": _B_in["v"],
        "B_shift_k": _B_in["shift_k"],
        "B_ssm_k": _B_in["ssm_k"],
        "B_ssm_D": _B_in["ssm_D"],
    }

def reference(A_x, A_dft_seq_re, A_dft_seq_im, A_dft_hid_re, A_dft_hid_im, B_q, B_k, B_v, B_shift_k, B_ssm_k, B_ssm_D):
    def _A_ref(x, dft_seq_re, dft_seq_im, dft_hid_re, dft_hid_im):
        a = torch.einsum("bsd,ed->bse", x, dft_hid_re)
        b = torch.einsum("bsd,ed->bse", x, dft_hid_im)
        y = torch.einsum("ts,bse->bte", dft_seq_re, a) - torch.einsum("ts,bse->bte", dft_seq_im, b)
        return y

    def _B_ref(q, k, v, shift_k, ssm_k, ssm_D):
        B, S, D = q.shape
        ks = shift_k.shape[-1]
        k_pad = _pad(k, ((0, 0), (ks - 1, 0), (0, 0)))
        k_shift = torch.zeros_like(k)
        for t in range(ks):
            k_shift = k_shift + k_pad[:, t:t + S, :] * shift_k[:, ks - 1 - t][None, None, :]
        kv = k_shift * v
        L = 2 * S
        kv_pad = _pad(kv, ((0, 0), (0, S), (0, 0)))
        kf_pad = _pad(ssm_k, ((0, 0), (0, S)))
        kv_f = (lambda x, axes=(-2,-1): torch.fft.rfft2(x.float(), dim=axes))(kv_pad[:, None, :, :], axes=(1, 2))
        kf_f = (lambda x, axes=(-2,-1): torch.fft.rfft2(x.float(), dim=axes))(kf_pad[:, None, :], axes=(1, 2))
        kf_f = (lambda x, *d: x.permute(*d))(kf_f, 1, 2, 0)
        y_f = kv_f * kf_f[None, :, :, :]
        y = (lambda x, s, axes=(-2,-1): torch.fft.irfft2(x, s=s, dim=axes).to(torch.bfloat16))(y_f, (1, L), axes=(1, 2))[:, 0, :S, :]
        y = y + kv * ssm_D[None, None, :]
        return q * y

    a = _A_ref(A_x, A_dft_seq_re, A_dft_seq_im, A_dft_hid_re, A_dft_hid_im)
    b = _B_ref(B_q, B_k, B_v, B_shift_k, B_ssm_k, B_ssm_D)
    return torch.concatenate([a, b], axis=-1)
```

```cpp
#include <cuda_runtime.h>
#include <cuda.h>
#include <cuda_bf16.h>
#include <stdint.h>

#define STAGES 4
#define NCTA 128
#define A_BYTES 16384
#define B_BYTES 20480
#define STAGE_BYTES 36864
#define NTHREADS 512

#define OFF_PART   (STAGES * STAGE_BYTES)
#define OFF_CB     (OFF_PART + 32768)
#define CB_H0      64
#define CB_H1      4352
#define CB_U       8448
#define CB_BYTES   12672
#define OFF_BAR    (OFF_CB + 2 * CB_BYTES)
#define SMEM_BYTES (OFF_BAR + 256 + 1024)

__device__ __align__(1024) unsigned char g_ab[8 * 32 * B_BYTES];
__device__ __align__(1024) unsigned char g_kv[640 * 4096];
__device__ __align__(1024) unsigned char g_z[128 * 640 * 32];
__device__ unsigned g_flag_ab[256];
__device__ unsigned g_ticket;
__device__ unsigned g_kv_ready;
__device__ unsigned g_z_ready;
#define STAMP(i) do {} while (0)

template<int N> __device__ __forceinline__ void wgmma_ss(float* d, uint64_t a, uint64_t b, int s);
template<int N> __device__ __forceinline__ void wgmma_rs(float* d, uint32_t a0, uint32_t a1, uint32_t a2, uint32_t a3, uint64_t b, int s);
template<> __device__ __forceinline__ void wgmma_ss<160>(float* d, uint64_t descA, uint64_t descB, int scaleD) {
  asm volatile("{\n.reg .pred p;\nsetp.ne.b32 p, %82, 0;\n"
    "wgmma.mma_async.sync.aligned.m64n160k16.f32.bf16.bf16 {%0,%1,%2,%3,%4,%5,%6,%7,%8,%9,%10,%11,%12,%13,%14,%15,%16,%17,%18,%19,%20,%21,%22,%23,%24,%25,%26,%27,%28,%29,%30,%31,%32,%33,%34,%35,%36,%37,%38,%39,%40,%41,%42,%43,%44,%45,%46,%47,%48,%49,%50,%51,%52,%53,%54,%55,%56,%57,%58,%59,%60,%61,%62,%63,%64,%65,%66,%67,%68,%69,%70,%71,%72,%73,%74,%75,%76,%77,%78,%79}, %80, %81, p, 1, 1, 0, 0;\n}\n"
    : "+f"(d[0]),"+f"(d[1]),"+f"(d[2]),"+f"(d[3]),"+f"(d[4]),"+f"(d[5]),"+f"(d[6]),"+f"(d[7]),"+f"(d[8]),"+f"(d[9]),"+f"(d[10]),"+f"(d[11]),"+f"(d[12]),"+f"(d[13]),"+f"(d[14]),"+f"(d[15]),"+f"(d[16]),"+f"(d[17]),"+f"(d[18]),"+f"(d[19]),"+f"(d[20]),"+f"(d[21]),"+f"(d[22]),"+f"(d[23]),"+f"(d[24]),"+f"(d[25]),"+f"(d[26]),"+f"(d[27]),"+f"(d[28]),"+f"(d[29]),"+f"(d[30]),"+f"(d[31]),"+f"(d[32]),"+f"(d[33]),"+f"(d[34]),"+f"(d[35]),"+f"(d[36]),"+f"(d[37]),"+f"(d[38]),"+f"(d[39]),"+f"(d[40]),"+f"(d[41]),"+f"(d[42]),"+f"(d[43]),"+f"(d[44]),"+f"(d[45]),"+f"(d[46]),"+f"(d[47]),"+f"(d[48]),"+f"(d[49]),"+f"(d[50]),"+f"(d[51]),"+f"(d[52]),"+f"(d[53]),"+f"(d[54]),"+f"(d[55]),"+f"(d[56]),"+f"(d[57]),"+f"(d[58]),"+f"(d[59]),"+f"(d[60]),"+f"(d[61]),"+f"(d[62]),"+f"(d[63]),"+f"(d[64]),"+f"(d[65]),"+f"(d[66]),"+f"(d[67]),"+f"(d[68]),"+f"(d[69]),"+f"(d[70]),"+f"(d[71]),"+f"(d[72]),"+f"(d[73]),"+f"(d[74]),"+f"(d[75]),"+f"(d[76]),"+f"(d[77]),"+f"(d[78]),"+f"(d[79])
    : "l"(descA),"l"(descB),"r"(scaleD));
}
template<> __device__ __forceinline__ void wgmma_rs<8>(float* d, uint32_t a0, uint32_t a1, uint32_t a2, uint32_t a3, uint64_t descB, int scaleD) {
  asm volatile("{\n.reg .pred p;\nsetp.ne.b32 p, %9, 0;\n"
    "wgmma.mma_async.sync.aligned.m64n8k16.f32.bf16.bf16 {%0,%1,%2,%3}, {%4,%5,%6,%7}, %8, p, 1, 1, 0;\n}\n"
    : "+f"(d[0]),"+f"(d[1]),"+f"(d[2]),"+f"(d[3])
    : "r"(a0),"r"(a1),"r"(a2),"r"(a3),"l"(descB),"r"(scaleD));
}
template<> __device__ __forceinline__ void wgmma_rs<16>(float* d, uint32_t a0, uint32_t a1, uint32_t a2, uint32_t a3, uint64_t descB, int scaleD) {
  asm volatile("{\n.reg .pred p;\nsetp.ne.b32 p, %13, 0;\n"
    "wgmma.mma_async.sync.aligned.m64n16k16.f32.bf16.bf16 {%0,%1,%2,%3,%4,%5,%6,%7}, {%8,%9,%10,%11}, %12, p, 1, 1, 0;\n}\n"
    : "+f"(d[0]),"+f"(d[1]),"+f"(d[2]),"+f"(d[3]),"+f"(d[4]),"+f"(d[5]),"+f"(d[6]),"+f"(d[7])
    : "r"(a0),"r"(a1),"r"(a2),"r"(a3),"l"(descB),"r"(scaleD));
}
template<> __device__ __forceinline__ void wgmma_rs<24>(float* d, uint32_t a0, uint32_t a1, uint32_t a2, uint32_t a3, uint64_t descB, int scaleD) {
  asm volatile("{\n.reg .pred p;\nsetp.ne.b32 p, %17, 0;\n"
    "wgmma.mma_async.sync.aligned.m64n24k16.f32.bf16.bf16 {%0,%1,%2,%3,%4,%5,%6,%7,%8,%9,%10,%11}, {%12,%13,%14,%15}, %16, p, 1, 1, 0;\n}\n"
    : "+f"(d[0]),"+f"(d[1]),"+f"(d[2]),"+f"(d[3]),"+f"(d[4]),"+f"(d[5]),"+f"(d[6]),"+f"(d[7]),"+f"(d[8]),"+f"(d[9]),"+f"(d[10]),"+f"(d[11])
    : "r"(a0),"r"(a1),"r"(a2),"r"(a3),"l"(descB),"r"(scaleD));
}
template<> __device__ __forceinline__ void wgmma_rs<32>(float* d, uint32_t a0, uint32_t a1, uint32_t a2, uint32_t a3, uint64_t descB, int scaleD) {
  asm volatile("{\n.reg .pred p;\nsetp.ne.b32 p, %21, 0;\n"
    "wgmma.mma_async.sync.aligned.m64n32k16.f32.bf16.bf16 {%0,%1,%2,%3,%4,%5,%6,%7,%8,%9,%10,%11,%12,%13,%14,%15}, {%16,%17,%18,%19}, %20, p, 1, 1, 0;\n}\n"
    : "+f"(d[0]),"+f"(d[1]),"+f"(d[2]),"+f"(d[3]),"+f"(d[4]),"+f"(d[5]),"+f"(d[6]),"+f"(d[7]),"+f"(d[8]),"+f"(d[9]),"+f"(d[10]),"+f"(d[11]),"+f"(d[12]),"+f"(d[13]),"+f"(d[14]),"+f"(d[15])
    : "r"(a0),"r"(a1),"r"(a2),"r"(a3),"l"(descB),"r"(scaleD));
}
template<> __device__ __forceinline__ void wgmma_rs<40>(float* d, uint32_t a0, uint32_t a1, uint32_t a2, uint32_t a3, uint64_t descB, int scaleD) {
  asm volatile("{\n.reg .pred p;\nsetp.ne.b32 p, %25, 0;\n"
    "wgmma.mma_async.sync.aligned.m64n40k16.f32.bf16.bf16 {%0,%1,%2,%3,%4,%5,%6,%7,%8,%9,%10,%11,%12,%13,%14,%15,%16,%17,%18,%19}, {%20,%21,%22,%23}, %24, p, 1, 1, 0;\n}\n"
    : "+f"(d[0]),"+f"(d[1]),"+f"(d[2]),"+f"(d[3]),"+f"(d[4]),"+f"(d[5]),"+f"(d[6]),"+f"(d[7]),"+f"(d[8]),"+f"(d[9]),"+f"(d[10]),"+f"(d[11]),"+f"(d[12]),"+f"(d[13]),"+f"(d[14]),"+f"(d[15]),"+f"(d[16]),"+f"(d[17]),"+f"(d[18]),"+f"(d[19])
    : "r"(a0),"r"(a1),"r"(a2),"r"(a3),"l"(descB),"r"(scaleD));
}
template<> __device__ __forceinline__ void wgmma_rs<48>(float* d, uint32_t a0, uint32_t a1, uint32_t a2, uint32_t a3, uint64_t descB, int scaleD) {
  asm volatile("{\n.reg .pred p;\nsetp.ne.b32 p, %29, 0;\n"
    "wgmma.mma_async.sync.aligned.m64n48k16.f32.bf16.bf16 {%0,%1,%2,%3,%4,%5,%6,%7,%8,%9,%10,%11,%12,%13,%14,%15,%16,%17,%18,%19,%20,%21,%22,%23}, {%24,%25,%26,%27}, %28, p, 1, 1, 0;\n}\n"
    : "+f"(d[0]),"+f"(d[1]),"+f"(d[2]),"+f"(d[3]),"+f"(d[4]),"+f"(d[5]),"+f"(d[6]),"+f"(d[7]),"+f"(d[8]),"+f"(d[9]),"+f"(d[10]),"+f"(d[11]),"+f"(d[12]),"+f"(d[13]),"+f"(d[14]),"+f"(d[15]),"+f"(d[16]),"+f"(d[17]),"+f"(d[18]),"+f"(d[19]),"+f"(d[20]),"+f"(d[21]),"+f"(d[22]),"+f"(d[23])
    : "r"(a0),"r"(a1),"r"(a2),"r"(a3),"l"(descB),"r"(scaleD));
}
template<> __device__ __forceinline__ void wgmma_rs<56>(float* d, uint32_t a0, uint32_t a1, uint32_t a2, uint32_t a3, uint64_t descB, int scaleD) {
  asm volatile("{\n.reg .pred p;\nsetp.ne.b32 p, %33, 0;\n"
    "wgmma.mma_async.sync.aligned.m64n56k16.f32.bf16.bf16 {%0,%1,%2,%3,%4,%5,%6,%7,%8,%9,%10,%11,%12,%13,%14,%15,%16,%17,%18,%19,%20,%21,%22,%23,%24,%25,%26,%27}, {%28,%29,%30,%31}, %32, p, 1, 1, 0;\n}\n"
    : "+f"(d[0]),"+f"(d[1]),"+f"(d[2]),"+f"(d[3]),"+f"(d[4]),"+f"(d[5]),"+f"(d[6]),"+f"(d[7]),"+f"(d[8]),"+f"(d[9]),"+f"(d[10]),"+f"(d[11]),"+f"(d[12]),"+f"(d[13]),"+f"(d[14]),"+f"(d[15]),"+f"(d[16]),"+f"(d[17]),"+f"(d[18]),"+f"(d[19]),"+f"(d[20]),"+f"(d[21]),"+f"(d[22]),"+f"(d[23]),"+f"(d[24]),"+f"(d[25]),"+f"(d[26]),"+f"(d[27])
    : "r"(a0),"r"(a1),"r"(a2),"r"(a3),"l"(descB),"r"(scaleD));
}
template<> __device__ __forceinline__ void wgmma_rs<64>(float* d, uint32_t a0, uint32_t a1, uint32_t a2, uint32_t a3, uint64_t descB, int scaleD) {
  asm volatile("{\n.reg .pred p;\nsetp.ne.b32 p, %37, 0;\n"
    "wgmma.mma_async.sync.aligned.m64n64k16.f32.bf16.bf16 {%0,%1,%2,%3,%4,%5,%6,%7,%8,%9,%10,%11,%12,%13,%14,%15,%16,%17,%18,%19,%20,%21,%22,%23,%24,%25,%26,%27,%28,%29,%30,%31}, {%32,%33,%34,%35}, %36, p, 1, 1, 0;\n}\n"
    : "+f"(d[0]),"+f"(d[1]),"+f"(d[2]),"+f"(d[3]),"+f"(d[4]),"+f"(d[5]),"+f"(d[6]),"+f"(d[7]),"+f"(d[8]),"+f"(d[9]),"+f"(d[10]),"+f"(d[11]),"+f"(d[12]),"+f"(d[13]),"+f"(d[14]),"+f"(d[15]),"+f"(d[16]),"+f"(d[17]),"+f"(d[18]),"+f"(d[19]),"+f"(d[20]),"+f"(d[21]),"+f"(d[22]),"+f"(d[23]),"+f"(d[24]),"+f"(d[25]),"+f"(d[26]),"+f"(d[27]),"+f"(d[28]),"+f"(d[29]),"+f"(d[30]),"+f"(d[31])
    : "r"(a0),"r"(a1),"r"(a2),"r"(a3),"l"(descB),"r"(scaleD));
}
template<> __device__ __forceinline__ void wgmma_rs<72>(float* d, uint32_t a0, uint32_t a1, uint32_t a2, uint32_t a3, uint64_t descB, int scaleD) {
  asm volatile("{\n.reg .pred p;\nsetp.ne.b32 p, %41, 0;\n"
    "wgmma.mma_async.sync.aligned.m64n72k16.f32.bf16.bf16 {%0,%1,%2,%3,%4,%5,%6,%7,%8,%9,%10,%11,%12,%13,%14,%15,%16,%17,%18,%19,%20,%21,%22,%23,%24,%25,%26,%27,%28,%29,%30,%31,%32,%33,%34,%35}, {%36,%37,%38,%39}, %40, p, 1, 1, 0;\n}\n"
    : "+f"(d[0]),"+f"(d[1]),"+f"(d[2]),"+f"(d[3]),"+f"(d[4]),"+f"(d[5]),"+f"(d[6]),"+f"(d[7]),"+f"(d[8]),"+f"(d[9]),"+f"(d[10]),"+f"(d[11]),"+f"(d[12]),"+f"(d[13]),"+f"(d[14]),"+f"(d[15]),"+f"(d[16]),"+f"(d[17]),"+f"(d[18]),"+f"(d[19]),"+f"(d[20]),"+f"(d[21]),"+f"(d[22]),"+f"(d[23]),"+f"(d[24]),"+f"(d[25]),"+f"(d[26]),"+f"(d[27]),"+f"(d[28]),"+f"(d[29]),"+f"(d[30]),"+f"(d[31]),"+f"(d[32]),"+f"(d[33]),"+f"(d[34]),"+f"(d[35])
    : "r"(a0),"r"(a1),"r"(a2),"r"(a3),"l"(descB),"r"(scaleD));
}
template<> __device__ __forceinline__ void wgmma_rs<80>(float* d, uint32_t a0, uint32_t a1, uint32_t a2, uint32_t a3, uint64_t descB, int scaleD) {
  asm volatile("{\n.reg .pred p;\nsetp.ne.b32 p, %45, 0;\n"
    "wgmma.mma_async.sync.aligned.m64n80k16.f32.bf16.bf16 {%0,%1,%2,%3,%4,%5,%6,%7,%8,%9,%10,%11,%12,%13,%14,%15,%16,%17,%18,%19,%20,%21,%22,%23,%24,%25,%26,%27,%28,%29,%30,%31,%32,%33,%34,%35,%36,%37,%38,%39}, {%40,%41,%42,%43}, %44, p, 1, 1, 0;\n}\n"
    : "+f"(d[0]),"+f"(d[1]),"+f"(d[2]),"+f"(d[3]),"+f"(d[4]),"+f"(d[5]),"+f"(d[6]),"+f"(d[7]),"+f"(d[8]),"+f"(d[9]),"+f"(d[10]),"+f"(d[11]),"+f"(d[12]),"+f"(d[13]),"+f"(d[14]),"+f"(d[15]),"+f"(d[16]),"+f"(d[17]),"+f"(d[18]),"+f"(d[19]),"+f"(d[20]),"+f"(d[21]),"+f"(d[22]),"+f"(d[23]),"+f"(d[24]),"+f"(d[25]),"+f"(d[26]),"+f"(d[27]),"+f"(d[28]),"+f"(d[29]),"+f"(d[30]),"+f"(d[31]),"+f"(d[32]),"+f"(d[33]),"+f"(d[34]),"+f"(d[35]),"+f"(d[36]),"+f"(d[37]),"+f"(d[38]),"+f"(d[39])
    : "r"(a0),"r"(a1),"r"(a2),"r"(a3),"l"(descB),"r"(scaleD));
}
template<> __device__ __forceinline__ void wgmma_rs<88>(float* d, uint32_t a0, uint32_t a1, uint32_t a2, uint32_t a3, uint64_t descB, int scaleD) {
  asm volatile("{\n.reg .pred p;\nsetp.ne.b32 p, %49, 0;\n"
    "wgmma.mma_async.sync.aligned.m64n88k16.f32.bf16.bf16 {%0,%1,%2,%3,%4,%5,%6,%7,%8,%9,%10,%11,%12,%13,%14,%15,%16,%17,%18,%19,%20,%21,%22,%23,%24,%25,%26,%27,%28,%29,%30,%31,%32,%33,%34,%35,%36,%37,%38,%39,%40,%41,%42,%43}, {%44,%45,%46,%47}, %48, p, 1, 1, 0;\n}\n"
    : "+f"(d[0]),"+f"(d[1]),"+f"(d[2]),"+f"(d[3]),"+f"(d[4]),"+f"(d[5]),"+f"(d[6]),"+f"(d[7]),"+f"(d[8]),"+f"(d[9]),"+f"(d[10]),"+f"(d[11]),"+f"(d[12]),"+f"(d[13]),"+f"(d[14]),"+f"(d[15]),"+f"(d[16]),"+f"(d[17]),"+f"(d[18]),"+f"(d[19]),"+f"(d[20]),"+f"(d[21]),"+f"(d[22]),"+f"(d[23]),"+f"(d[24]),"+f"(d[25]),"+f"(d[26]),"+f"(d[27]),"+f"(d[28]),"+f"(d[29]),"+f"(d[30]),"+f"(d[31]),"+f"(d[32]),"+f"(d[33]),"+f"(d[34]),"+f"(d[35]),"+f"(d[36]),"+f"(d[37]),"+f"(d[38]),"+f"(d[39]),"+f"(d[40]),"+f"(d[41]),"+f"(d[42]),"+f"(d[43])
    : "r"(a0),"r"(a1),"r"(a2),"r"(a3),"l"(descB),"r"(scaleD));
}
template<> __device__ __forceinline__ void wgmma_rs<96>(float* d, uint32_t a0, uint32_t a1, uint32_t a2, uint32_t a3, uint64_t descB, int scaleD) {
  asm volatile("{\n.reg .pred p;\nsetp.ne.b32 p, %53, 0;\n"
    "wgmma.mma_async.sync.aligned.m64n96k16.f32.bf16.bf16 {%0,%1,%2,%3,%4,%5,%6,%7,%8,%9,%10,%11,%12,%13,%14,%15,%16,%17,%18,%19,%20,%21,%22,%23,%24,%25,%26,%27,%28,%29,%30,%31,%32,%33,%34,%35,%36,%37,%38,%39,%40,%41,%42,%43,%44,%45,%46,%47}, {%48,%49,%50,%51}, %52, p, 1, 1, 0;\n}\n"
    : "+f"(d[0]),"+f"(d[1]),"+f"(d[2]),"+f"(d[3]),"+f"(d[4]),"+f"(d[5]),"+f"(d[6]),"+f"(d[7]),"+f"(d[8]),"+f"(d[9]),"+f"(d[10]),"+f"(d[11]),"+f"(d[12]),"+f"(d[13]),"+f"(d[14]),"+f"(d[15]),"+f"(d[16]),"+f"(d[17]),"+f"(d[18]),"+f"(d[19]),"+f"(d[20]),"+f"(d[21]),"+f"(d[22]),"+f"(d[23]),"+f"(d[24]),"+f"(d[25]),"+f"(d[26]),"+f"(d[27]),"+f"(d[28]),"+f"(d[29]),"+f"(d[30]),"+f"(d[31]),"+f"(d[32]),"+f"(d[33]),"+f"(d[34]),"+f"(d[35]),"+f"(d[36]),"+f"(d[37]),"+f"(d[38]),"+f"(d[39]),"+f"(d[40]),"+f"(d[41]),"+f"(d[42]),"+f"(d[43]),"+f"(d[44]),"+f"(d[45]),"+f"(d[46]),"+f"(d[47])
    : "r"(a0),"r"(a1),"r"(a2),"r"(a3),"l"(descB),"r"(scaleD));
}
template<> __device__ __forceinline__ void wgmma_rs<104>(float* d, uint32_t a0, uint32_t a1, uint32_t a2, uint32_t a3, uint64_t descB, int scaleD) {
  asm volatile("{\n.reg .pred p;\nsetp.ne.b32 p, %57, 0;\n"
    "wgmma.mma_async.sync.aligned.m64n104k16.f32.bf16.bf16 {%0,%1,%2,%3,%4,%5,%6,%7,%8,%9,%10,%11,%12,%13,%14,%15,%16,%17,%18,%19,%20,%21,%22,%23,%24,%25,%26,%27,%28,%29,%30,%31,%32,%33,%34,%35,%36,%37,%38,%39,%40,%41,%42,%43,%44,%45,%46,%47,%48,%49,%50,%51}, {%52,%53,%54,%55}, %56, p, 1, 1, 0;\n}\n"
    : "+f"(d[0]),"+f"(d[1]),"+f"(d[2]),"+f"(d[3]),"+f"(d[4]),"+f"(d[5]),"+f"(d[6]),"+f"(d[7]),"+f"(d[8]),"+f"(d[9]),"+f"(d[10]),"+f"(d[11]),"+f"(d[12]),"+f"(d[13]),"+f"(d[14]),"+f"(d[15]),"+f"(d[16]),"+f"(d[17]),"+f"(d[18]),"+f"(d[19]),"+f"(d[20]),"+f"(d[21]),"+f"(d[22]),"+f"(d[23]),"+f"(d[24]),"+f"(d[25]),"+f"(d[26]),"+f"(d[27]),"+f"(d[28]),"+f"(d[29]),"+f"(d[30]),"+f"(d[31]),"+f"(d[32]),"+f"(d[33]),"+f"(d[34]),"+f"(d[35]),"+f"(d[36]),"+f"(d[37]),"+f"(d[38]),"+f"(d[39]),"+f"(d[40]),"+f"(d[41]),"+f"(d[42]),"+f"(d[43]),"+f"(d[44]),"+f"(d[45]),"+f"(d[46]),"+f"(d[47]),"+f"(d[48]),"+f"(d[49]),"+f"(d[50]),"+f"(d[51])
    : "r"(a0),"r"(a1),"r"(a2),"r"(a3),"l"(descB),"r"(scaleD));
}
template<> __device__ __forceinline__ void wgmma_rs<112>(float* d, uint32_t a0, uint32_t a1, uint32_t a2, uint32_t a3, uint64_t descB, int scaleD) {
  asm volatile("{\n.reg .pred p;\nsetp.ne.b32 p, %61, 0;\n"
    "wgmma.mma_async.sync.aligned.m64n112k16.f32.bf16.bf16 {%0,%1,%2,%3,%4,%5,%6,%7,%8,%9,%10,%11,%12,%13,%14,%15,%16,%17,%18,%19,%20,%21,%22,%23,%24,%25,%26,%27,%28,%29,%30,%31,%32,%33,%34,%35,%36,%37,%38,%39,%40,%41,%42,%43,%44,%45,%46,%47,%48,%49,%50,%51,%52,%53,%54,%55}, {%56,%57,%58,%59}, %60, p, 1, 1, 0;\n}\n"
    : "+f"(d[0]),"+f"(d[1]),"+f"(d[2]),"+f"(d[3]),"+f"(d[4]),"+f"(d[5]),"+f"(d[6]),"+f"(d[7]),"+f"(d[8]),"+f"(d[9]),"+f"(d[10]),"+f"(d[11]),"+f"(d[12]),"+f"(d[13]),"+f"(d[14]),"+f"(d[15]),"+f"(d[16]),"+f"(d[17]),"+f"(d[18]),"+f"(d[19]),"+f"(d[20]),"+f"(d[21]),"+f"(d[22]),"+f"(d[23]),"+f"(d[24]),"+f"(d[25]),"+f"(d[26]),"+f"(d[27]),"+f"(d[28]),"+f"(d[29]),"+f"(d[30]),"+f"(d[31]),"+f"(d[32]),"+f"(d[33]),"+f"(d[34]),"+f"(d[35]),"+f"(d[36]),"+f"(d[37]),"+f"(d[38]),"+f"(d[39]),"+f"(d[40]),"+f"(d[41]),"+f"(d[42]),"+f"(d[43]),"+f"(d[44]),"+f"(d[45]),"+f"(d[46]),"+f"(d[47]),"+f"(d[48]),"+f"(d[49]),"+f"(d[50]),"+f"(d[51]),"+f"(d[52]),"+f"(d[53]),"+f"(d[54]),"+f"(d[55])
    : "r"(a0),"r"(a1),"r"(a2),"r"(a3),"l"(descB),"r"(scaleD));
}
template<> __device__ __forceinline__ void wgmma_rs<120>(float* d, uint32_t a0, uint32_t a1, uint32_t a2, uint32_t a3, uint64_t descB, int scaleD) {
  asm volatile("{\n.reg .pred p;\nsetp.ne.b32 p, %65, 0;\n"
    "wgmma.mma_async.sync.aligned.m64n120k16.f32.bf16.bf16 {%0,%1,%2,%3,%4,%5,%6,%7,%8,%9,%10,%11,%12,%13,%14,%15,%16,%17,%18,%19,%20,%21,%22,%23,%24,%25,%26,%27,%28,%29,%30,%31,%32,%33,%34,%35,%36,%37,%38,%39,%40,%41,%42,%43,%44,%45,%46,%47,%48,%49,%50,%51,%52,%53,%54,%55,%56,%57,%58,%59}, {%60,%61,%62,%63}, %64, p, 1, 1, 0;\n}\n"
    : "+f"(d[0]),"+f"(d[1]),"+f"(d[2]),"+f"(d[3]),"+f"(d[4]),"+f"(d[5]),"+f"(d[6]),"+f"(d[7]),"+f"(d[8]),"+f"(d[9]),"+f"(d[10]),"+f"(d[11]),"+f"(d[12]),"+f"(d[13]),"+f"(d[14]),"+f"(d[15]),"+f"(d[16]),"+f"(d[17]),"+f"(d[18]),"+f"(d[19]),"+f"(d[20]),"+f"(d[21]),"+f"(d[22]),"+f"(d[23]),"+f"(d[24]),"+f"(d[25]),"+f"(d[26]),"+f"(d[27]),"+f"(d[28]),"+f"(d[29]),"+f"(d[30]),"+f"(d[31]),"+f"(d[32]),"+f"(d[33]),"+f"(d[34]),"+f"(d[35]),"+f"(d[36]),"+f"(d[37]),"+f"(d[38]),"+f"(d[39]),"+f"(d[40]),"+f"(d[41]),"+f"(d[42]),"+f"(d[43]),"+f"(d[44]),"+f"(d[45]),"+f"(d[46]),"+f"(d[47]),"+f"(d[48]),"+f"(d[49]),"+f"(d[50]),"+f"(d[51]),"+f"(d[52]),"+f"(d[53]),"+f"(d[54]),"+f"(d[55]),"+f"(d[56]),"+f"(d[57]),"+f"(d[58]),"+f"(d[59])
    : "r"(a0),"r"(a1),"r"(a2),"r"(a3),"l"(descB),"r"(scaleD));
}
template<> __device__ __forceinline__ void wgmma_rs<128>(float* d, uint32_t a0, uint32_t a1, uint32_t a2, uint32_t a3, uint64_t descB, int scaleD) {
  asm volatile("{\n.reg .pred p;\nsetp.ne.b32 p, %69, 0;\n"
    "wgmma.mma_async.sync.aligned.m64n128k16.f32.bf16.bf16 {%0,%1,%2,%3,%4,%5,%6,%7,%8,%9,%10,%11,%12,%13,%14,%15,%16,%17,%18,%19,%20,%21,%22,%23,%24,%25,%26,%27,%28,%29,%30,%31,%32,%33,%34,%35,%36,%37,%38,%39,%40,%41,%42,%43,%44,%45,%46,%47,%48,%49,%50,%51,%52,%53,%54,%55,%56,%57,%58,%59,%60,%61,%62,%63}, {%64,%65,%66,%67}, %68, p, 1, 1, 0;\n}\n"
    : "+f"(d[0]),"+f"(d[1]),"+f"(d[2]),"+f"(d[3]),"+f"(d[4]),"+f"(d[5]),"+f"(d[6]),"+f"(d[7]),"+f"(d[8]),"+f"(d[9]),"+f"(d[10]),"+f"(d[11]),"+f"(d[12]),"+f"(d[13]),"+f"(d[14]),"+f"(d[15]),"+f"(d[16]),"+f"(d[17]),"+f"(d[18]),"+f"(d[19]),"+f"(d[20]),"+f"(d[21]),"+f"(d[22]),"+f"(d[23]),"+f"(d[24]),"+f"(d[25]),"+f"(d[26]),"+f"(d[27]),"+f"(d[28]),"+f"(d[29]),"+f"(d[30]),"+f"(d[31]),"+f"(d[32]),"+f"(d[33]),"+f"(d[34]),"+f"(d[35]),"+f"(d[36]),"+f"(d[37]),"+f"(d[38]),"+f"(d[39]),"+f"(d[40]),"+f"(d[41]),"+f"(d[42]),"+f"(d[43]),"+f"(d[44]),"+f"(d[45]),"+f"(d[46]),"+f"(d[47]),"+f"(d[48]),"+f"(d[49]),"+f"(d[50]),"+f"(d[51]),"+f"(d[52]),"+f"(d[53]),"+f"(d[54]),"+f"(d[55]),"+f"(d[56]),"+f"(d[57]),"+f"(d[58]),"+f"(d[59]),"+f"(d[60]),"+f"(d[61]),"+f"(d[62]),"+f"(d[63])
    : "r"(a0),"r"(a1),"r"(a2),"r"(a3),"l"(descB),"r"(scaleD));
}

__device__ __forceinline__ uint32_t smem_u32(const void* p) { return (uint32_t)__cvta_generic_to_shared(p); }
__device__ __forceinline__ uint64_t mkdesc(uint32_t addr, uint32_t lbo, uint32_t sbo, int swz) {
  return (uint64_t)((addr & 0x3FFFF) >> 4) | ((uint64_t)(lbo >> 4) << 16) | ((uint64_t)(sbo >> 4) << 32) | ((uint64_t)swz << 62);
}
__device__ __forceinline__ unsigned long long gtime() { unsigned long long t; asm volatile("mov.u64 %0, %%globaltimer;" : "=l"(t)); return t; }
__device__ __forceinline__ void mbar_init(uint32_t bar, int count) { asm volatile("mbarrier.init.shared::cta.b64 [%0], %1;" ::"r"(bar), "r"(count) : "memory"); }
__device__ __forceinline__ void mbar_expect_tx(uint32_t bar, uint32_t bytes) { asm volatile("mbarrier.arrive.expect_tx.shared::cta.b64 _, [%0], %1;" ::"r"(bar), "r"(bytes) : "memory"); }
__device__ __forceinline__ void mbar_arrive(uint32_t bar) { asm volatile("mbarrier.arrive.shared::cta.b64 _, [%0];" ::"r"(bar) : "memory"); }
__device__ __forceinline__ void mbar_arrive_cta(uint32_t bar, uint32_t cta) {
  asm volatile("{\n.reg .b32 ra;\nmapa.shared::cluster.u32 ra, %0, %1;\nmbarrier.arrive.shared::cluster.b64 _, [ra];\n}\n" ::"r"(bar), "r"(cta) : "memory");
}
__device__ __forceinline__ void mbar_wait(uint32_t bar, uint32_t parity) {
  uint32_t ok;
  int tries = 0;
  do {
    asm volatile("{\n.reg .pred p;\nmbarrier.try_wait.parity.shared::cta.b64 p, [%1], %2;\nselp.u32 %0, 1, 0, p;\n}\n" : "=r"(ok) : "r"(bar), "r"(parity) : "memory");
    if (!ok && ++tries > (1 << 22)) __trap();
  } while (!ok);
}
__device__ __forceinline__ void tma_load_2d(uint32_t dst, const CUtensorMap* map, int c0, int c1, uint32_t bar) {
  asm volatile("cp.async.bulk.tensor.2d.shared::cluster.global.mbarrier::complete_tx::bytes [%0], [%1, {%3, %4}], [%2];"
               ::"r"(dst), "l"((uint64_t)map), "r"(bar), "r"(c0), "r"(c1) : "memory");
}
__device__ __forceinline__ void tma_load_2d_mc(uint32_t dst, const CUtensorMap* map, int c0, int c1, uint32_t bar, uint16_t mask) {
  asm volatile("cp.async.bulk.tensor.2d.shared::cluster.global.mbarrier::complete_tx::bytes.multicast::cluster [%0], [%1, {%3, %4}], [%2], %5;"
               ::"r"(dst), "l"((uint64_t)map), "r"(bar), "r"(c0), "r"(c1), "h"(mask) : "memory");
}
__device__ __forceinline__ void tma_prefetch_2d(const CUtensorMap* map, int c0, int c1) {
  asm volatile("cp.async.bulk.prefetch.tensor.2d.L2.global [%0, {%1, %2}];" ::"l"((uint64_t)map), "r"(c0), "r"(c1) : "memory");
}
__device__ __forceinline__ void bulk_load(uint32_t dst, const void* src, uint32_t bytes, uint32_t bar) {
  asm volatile("cp.async.bulk.shared::cluster.global.mbarrier::complete_tx::bytes [%0], [%1], %2, [%3];"
               ::"r"(dst), "l"((uint64_t)src), "r"(bytes), "r"(bar) : "memory");
}
__device__ __forceinline__ void bulk_store(void* dst, uint32_t src, uint32_t bytes) {
  asm volatile("cp.async.bulk.global.shared::cta.bulk_group [%0], [%1], %2;" ::"l"((uint64_t)dst), "r"(src), "r"(bytes) : "memory");
}
__device__ __forceinline__ void bulk_prefetch(const void* src, uint32_t bytes) {
  asm volatile("cp.async.bulk.prefetch.L2.global [%0], %1;" ::"l"((uint64_t)src), "r"(bytes) : "memory");
}
__device__ __forceinline__ void tma_reduce_add_2d(const CUtensorMap* map, int c0, int c1, uint32_t src) {
  asm volatile("cp.reduce.async.bulk.tensor.2d.global.shared::cta.add.tile.bulk_group [%0, {%1, %2}], [%3];"
               ::"l"((uint64_t)map), "r"(c0), "r"(c1), "r"(src) : "memory");
}
__device__ __forceinline__ void bulk_commit() { asm volatile("cp.async.bulk.commit_group;" ::: "memory"); }
__device__ __forceinline__ void bulk_wait_all() { asm volatile("cp.async.bulk.wait_group 0;" ::: "memory"); }
__device__ __forceinline__ void bulk_wait_read() { asm volatile("cp.async.bulk.wait_group.read 0;" ::: "memory"); }
__device__ __forceinline__ void fence_async_smem() { asm volatile("fence.proxy.async.shared::cta;" ::: "memory"); }
__device__ __forceinline__ void fence_async_all() { asm volatile("fence.proxy.async;" ::: "memory"); }
__device__ __forceinline__ void cluster_arrive() { asm volatile("barrier.cluster.arrive.release.aligned;" ::: "memory"); }
__device__ __forceinline__ void cluster_wait() { asm volatile("barrier.cluster.wait.acquire.aligned;" ::: "memory"); }
__device__ __forceinline__ uint32_t cluster_rank() { uint32_t r; asm volatile("mov.u32 %0, %%cluster_ctarank;" : "=r"(r)); return r; }
__device__ __forceinline__ void wg_fence() { asm volatile("wgmma.fence.sync.aligned;" ::: "memory"); }
__device__ __forceinline__ void wg_commit() { asm volatile("wgmma.commit_group.sync.aligned;" ::: "memory"); }
template <int N> __device__ __forceinline__ void wg_wait() { asm volatile("wgmma.wait_group.sync.aligned %0;" ::"n"(N) : "memory"); }
template <int ID, int N> __device__ __forceinline__ void bar_sync() { asm volatile("bar.sync %0, %1;" ::"n"(ID), "n"(N) : "memory"); }
template <int R> __device__ __forceinline__ void reg_inc() { asm volatile("setmaxnreg.inc.sync.aligned.u32 %0;" ::"n"(R)); }
template <int R> __device__ __forceinline__ void reg_dec() { asm volatile("setmaxnreg.dec.sync.aligned.u32 %0;" ::"n"(R)); }
__device__ __forceinline__ unsigned ld_acquire(const unsigned* p) { unsigned v; asm volatile("ld.acquire.gpu.global.u32 %0, [%1];" : "=r"(v) : "l"(p) : "memory"); return v; }
__device__ __forceinline__ void st_release(unsigned* p, unsigned v) { asm volatile("st.release.gpu.global.u32 [%0], %1;" ::"l"(p), "r"(v) : "memory"); }
__device__ __forceinline__ void red_release_add(unsigned* p, unsigned v) { asm volatile("red.release.gpu.global.add.u32 [%0], %1;" ::"l"(p), "r"(v) : "memory"); }
__device__ __forceinline__ void wait_ge(const unsigned* p, unsigned target) {
  int tries = 0;
  while ((int)(ld_acquire(p) - target) < 0) {
    __nanosleep(40);
    if (++tries > (1 << 22)) __trap();
  }
}
__device__ __forceinline__ uint32_t lds32(uint32_t a) { uint32_t v; asm volatile("ld.shared.u32 %0, [%1];" : "=r"(v) : "r"(a) : "memory"); return v; }
__device__ __forceinline__ uint4 lds128(uint32_t a) { uint4 v; asm volatile("ld.shared.v4.u32 {%0,%1,%2,%3}, [%4];" : "=r"(v.x), "=r"(v.y), "=r"(v.z), "=r"(v.w) : "r"(a) : "memory"); return v; }
__device__ __forceinline__ float4 lds128f(uint32_t a) { float4 v; asm volatile("ld.shared.v4.f32 {%0,%1,%2,%3}, [%4];" : "=f"(v.x), "=f"(v.y), "=f"(v.z), "=f"(v.w) : "r"(a) : "memory"); return v; }
__device__ __forceinline__ void sts32f(uint32_t a, float v) { asm volatile("st.shared.f32 [%0], %1;" ::"r"(a), "f"(v) : "memory"); }
__device__ __forceinline__ void sts128(uint32_t a, uint4 v) { asm volatile("st.shared.v4.u32 [%0], {%1,%2,%3,%4};" ::"r"(a), "r"(v.x), "r"(v.y), "r"(v.z), "r"(v.w) : "memory"); }
__device__ __forceinline__ void stmatrix_x4(uint32_t a, uint32_t r0, uint32_t r1, uint32_t r2, uint32_t r3) {
  asm volatile("stmatrix.sync.aligned.m8n8.x4.shared.b16 [%0], {%1,%2,%3,%4};" ::"r"(a), "r"(r0), "r"(r1), "r"(r2), "r"(r3) : "memory");
}
__device__ __forceinline__ void stmatrix_x4_trans(uint32_t a, uint32_t r0, uint32_t r1, uint32_t r2, uint32_t r3) {
  asm volatile("stmatrix.sync.aligned.m8n8.x4.trans.shared.b16 [%0], {%1,%2,%3,%4};" ::"r"(a), "r"(r0), "r"(r1), "r"(r2), "r"(r3) : "memory");
}
__device__ __forceinline__ uint32_t pack_bf16(float lo, float hi) {
  uint32_t r; asm("cvt.rn.bf16x2.f32 %0, %1, %2;" : "=r"(r) : "f"(hi), "f"(lo)); return r;
}
__device__ __forceinline__ uint32_t bmul2(uint32_t a, uint32_t b) { uint32_t r; asm("mul.rn.bf16x2 %0, %1, %2;" : "=r"(r) : "r"(a), "r"(b)); return r; }
__device__ __forceinline__ uint32_t badd2(uint32_t a, uint32_t b) { uint32_t r; asm("add.rn.bf16x2 %0, %1, %2;" : "=r"(r) : "r"(a), "r"(b)); return r; }
__device__ __forceinline__ uint32_t ldg32(const void* p) { uint32_t v; asm volatile("ld.global.nc.u32 %0, [%1];" : "=r"(v) : "l"(p)); return v; }

#define BAR_FULL(s)  (bars + 8 * (s))
#define BAR_EMPTY(s) (bars + 8 * (STAGES + (s)))
#define BAR_CFULL(b) (bars + 8 * (2 * STAGES + (b)))
#define BAR_EPOCH    (bars + 8 * (2 * STAGES + 2))
#define BAR_STG      (bars + 8 * (2 * STAGES + 3))
#define BAR_ZERO     (bars + 8 * (2 * STAGES + 4))
#define EPOCH_WORD   (bars + 8 * (2 * STAGES + 5))

#define CB 2
template <int I0>
__device__ __forceinline__ void conv_load(uint32_t (&f)[4 * CB], uint32_t hp) {
#pragma unroll
  for (int j = 0; j < CB; j++) {
    f[4 * j + 0] = lds32(hp + 128 * (I0 + j));
    f[4 * j + 1] = lds32(hp + 128 * (I0 + j) + 16);
    f[4 * j + 3] = lds32(hp + 128 * (I0 + j) + 32);
  }
#pragma unroll
  for (int j = 0; j < CB; j++) asm volatile("mov.b32 %0, %1;" : "=r"(f[4 * j + 2]) : "r"(f[4 * j + 1]));
}
template <int I0>
__device__ __forceinline__ void conv_steps(float* acc, uint32_t (&fa)[4 * CB], uint32_t (&fb)[4 * CB], uint32_t hp, uint64_t descU) {
  if constexpr (I0 < 32) {
    wg_fence();
#pragma unroll
    for (int j = 0; j < CB; j++)
      wgmma_rs<128 - 4 * I0>(acc, fa[4 * j], fa[4 * j + 1], fa[4 * j + 2], fa[4 * j + 3], descU + 4 * (I0 + j), (I0 + j) != 0);
    wg_commit();
    if constexpr (I0 + CB < 32) conv_load<I0 + CB>(fb, hp);
    wg_wait<0>();
#pragma unroll
    for (int i = 0; i < (128 - 4 * I0) / 2; i++) { float t; asm volatile("mov.b32 %0, %1;" : "=f"(t) : "f"(acc[i]) : "memory"); acc[i] = t; }
    conv_steps<I0 + CB>(acc, fb, fa, hp, descU);
  }
}

struct Params {
  const __nv_bfloat16 *q, *k, *v, *shift_k, *ssm_k, *ssm_D;
  __nv_bfloat16* out;
};

__global__ void __cluster_dims__(2, 1, 1) __launch_bounds__(NTHREADS, 1)
fused_kernel(const __grid_constant__ CUtensorMap mX, const __grid_constant__ CUtensorMap mHr, const __grid_constant__ CUtensorMap mHi,
             const __grid_constant__ CUtensorMap mCr, const __grid_constant__ CUtensorMap mCi,
             const __grid_constant__ CUtensorMap mOut, const Params p) {
  extern __shared__ unsigned char smem_raw[];
  const uint32_t base = (smem_u32(smem_raw) + 1023) & ~1023u;
  const uint32_t bars = base + OFF_BAR;
  const int tid = threadIdx.x;
  const int warp = tid >> 5, lane = tid & 31;
  const uint32_t rank = cluster_rank();
  const int cid = blockIdx.x >> 1;
  const int g1_sb = cid >> 2, g1_eb = ((cid & 3) << 1) | rank;
  const int g2_tb = cid >> 2, g2_half = (cid >> 1) & 1, g2_eb = ((cid & 1) << 1) | rank;

  if (tid == 0) {
    STAMP(0);
    for (int s = 0; s < STAGES; s++) { mbar_init(BAR_FULL(s), 1); mbar_init(BAR_EMPTY(s), 4); }
    mbar_init(BAR_CFULL(0), 1); mbar_init(BAR_CFULL(1), 1);
    mbar_init(BAR_EPOCH, 1); mbar_init(BAR_STG, 2); mbar_init(BAR_ZERO, 1);
    asm volatile("fence.mbarrier_init.release.cluster;" ::: "memory");
  }
  if (warp == 12 && lane == 0) {
    const CUtensorMap* mH = (g1_eb < 4) ? &mHr : &mHi;
    for (int kb = 0; kb < 10; kb++) {
      tma_prefetch_2d(&mX, kb * 64, g1_sb * 128 + rank * 64);
      tma_prefetch_2d(mH, kb * 64, (g1_eb & 3) * 160);
    }
  }
  __syncthreads();
  cluster_arrive();
  cluster_wait();

  if (warp >= 12) {
    reg_dec<40>();
    if (warp == 12) {
    const CUtensorMap* mC = g2_half ? &mCi : &mCr;
    const int crow = g2_tb * 128 + rank * 64;
    const unsigned char* absrc = g_ab + (size_t)(g2_half * 4 + g2_eb) * 32 * B_BYTES;
    int it = 0;
    if (lane == 0) {
      const CUtensorMap* mH = (g1_eb < 4) ? &mHr : &mHi;
      for (int kb = 0; kb < 10; kb++, it++) {
        const int s = it % STAGES;
        mbar_wait(BAR_EMPTY(s), ((it / STAGES) & 1) ^ 1);
        const uint32_t sa = base + s * STAGE_BYTES;
        mbar_expect_tx(BAR_FULL(s), STAGE_BYTES);
        tma_load_2d_mc(sa + rank * 8192, &mX, kb * 64, g1_sb * 128 + rank * 64, BAR_FULL(s), 3);
        tma_load_2d(sa + A_BYTES, mH, kb * 64, (g1_eb & 3) * 160, BAR_FULL(s));
        if (kb >= STAGES - 1) {
          tma_prefetch_2d(mC, (kb - (STAGES - 1)) * 128, crow);
          tma_prefetch_2d(mC, (kb - (STAGES - 1)) * 128 + 64, crow);
        }
      }
      for (int j = 0; j < STAGES; j++) {
        const int s = (it + j) % STAGES;
        mbar_wait(BAR_EMPTY(s), (((it + j) / STAGES) & 1) ^ 1);
        mbar_expect_tx(BAR_FULL(s), STAGE_BYTES);
        tma_load_2d_mc(base + s * STAGE_BYTES + rank * 8192, mC, j * 64, crow, BAR_FULL(s), 3);
      }
    }
    it = 10;
    __syncwarp();
    mbar_wait(BAR_EPOCH, 0);
    const unsigned tag = lds32(EPOCH_WORD) + 1;
    wait_ge(&g_flag_ab[(g2_half * 4 + g2_eb) * 32 + lane], tag);
    __syncwarp();
    if (lane == 0) {
      STAMP(4);
      mbar_wait(BAR_STG, 0);
      fence_async_all();
      constexpr int PF0 = 2 * (10 - (STAGES - 1));
      for (int j = 0; j < 32; j++, it++) {
        const int s = it % STAGES;
        const uint32_t sa = base + s * STAGE_BYTES;
        if (j >= STAGES) {
          mbar_wait(BAR_EMPTY(s), ((it / STAGES) & 1) ^ 1);
          mbar_expect_tx(BAR_FULL(s), STAGE_BYTES);
          tma_load_2d_mc(sa + rank * 8192, mC, j * 64, crow, BAR_FULL(s), 3);
        }
        bulk_load(sa + A_BYTES, absrc + (size_t)j * B_BYTES, B_BYTES, BAR_FULL(s));
        if (j + PF0 < 32) tma_prefetch_2d(mC, (j + PF0) * 64, crow);
      }
    }
    __syncwarp();
    }
    cluster_arrive();
    cluster_wait();
  } else if (warp < 8) {
    reg_inc<152>();
    const int wg = warp >> 2, w = warp & 3;
    float acc[80];
    int it = 0;
#pragma unroll 1
    for (int phase = 0; phase < 2; phase++) {
      const int nk = phase ? 32 : 10;
#pragma unroll 1
      for (int kb = 0; kb < nk; kb++, it++) {
        const int s = it % STAGES;
        mbar_wait(BAR_FULL(s), (it / STAGES) & 1);
        if (tid == 0 && kb == 0) STAMP(phase ? 5 : 1);
        const uint32_t sa = base + s * STAGE_BYTES + wg * 8192, sb = base + s * STAGE_BYTES + A_BYTES;
        const uint64_t da = mkdesc(sa, 16, 1024, 1), db = mkdesc(sb, 16, 1024, 1);
#pragma unroll
        for (int i = 0; i < 80; i++) asm volatile("" : "+f"(acc[i])::"memory");
        wg_fence();
        wgmma_ss<160>(acc, da, db, kb != 0);
        wgmma_ss<160>(acc, da + 2, db + 2, 1);
        wgmma_ss<160>(acc, da + 4, db + 4, 1);
        wgmma_ss<160>(acc, da + 6, db + 6, 1);
        wg_commit();
        if (kb > 0) {
          wg_wait<1>();
          if ((tid & 127) < 2) mbar_arrive_cta(BAR_EMPTY((it - 1) % STAGES), tid & 1);
        }
      }
      wg_wait<0>();
#pragma unroll
      for (int i = 0; i < 80; i++) asm volatile("" : "+f"(acc[i])::"memory");
      if (phase == 0 && (tid & 127) < 2) mbar_arrive_cta(BAR_EMPTY((it - 1) % STAGES), tid & 1);
      if (tid == 0) STAMP(phase ? 6 : 2);
      bar_sync<1, 256>();
      const int m = lane >> 3, i8 = lane & 7;
      if (phase == 0) {
        const uint32_t stg = base + wg * STAGE_BYTES + A_BYTES;
        const uint32_t ad = stg + ((m >> 1) * 8 + i8) * 128 + (((2 * w + (m & 1)) ^ i8) << 4);
#pragma unroll
        for (int G = 0; G < 20; G += 2) {
          stmatrix_x4_trans(ad + G * 1024, pack_bf16(acc[4 * G], acc[4 * G + 1]), pack_bf16(acc[4 * G + 2], acc[4 * G + 3]),
                            pack_bf16(acc[4 * G + 4], acc[4 * G + 5]), pack_bf16(acc[4 * G + 6], acc[4 * G + 7]));
        }
        fence_async_smem();
        if (wg) bar_sync<3, 128>(); else bar_sync<2, 128>();
        if ((tid & 127) == 0) {
          const int kblk = g1_sb * 2 + wg;
          bulk_store(g_ab + ((size_t)g1_eb * 32 + kblk) * B_BYTES, stg, B_BYTES);
          bulk_commit();
          mbar_wait(BAR_EPOCH, 0);
          const unsigned tag = lds32(EPOCH_WORD) + 1;
          bulk_wait_all();
          mbar_arrive(BAR_STG);
          __threadfence();
          st_release(&g_flag_ab[g1_eb * 32 + kblk], tag);
          if (tid == 0) STAMP(3);
        }
      } else {
        const uint32_t stg = base + wg * B_BYTES;
        const uint32_t sgn = g2_half ? 0x80008000u : 0u;
        const int row = 16 * w + 8 * (m & 1) + i8;
#pragma unroll
        for (int G = 0; G < 20; G += 2) {
          const int Gc = G + (m >> 1);
          const uint32_t ad = stg + (Gc >> 2) * 4096 + row * 64 + (((Gc & 3) ^ ((row >> 1) & 3)) << 4);
          stmatrix_x4(ad, pack_bf16(acc[4 * G], acc[4 * G + 1]) ^ sgn, pack_bf16(acc[4 * G + 2], acc[4 * G + 3]) ^ sgn,
                      pack_bf16(acc[4 * G + 4], acc[4 * G + 5]) ^ sgn, pack_bf16(acc[4 * G + 6], acc[4 * G + 7]) ^ sgn);
        }
        fence_async_smem();
        if (wg) bar_sync<3, 128>(); else bar_sync<2, 128>();
        if ((tid & 127) == 0) {
          mbar_wait(BAR_ZERO, 0);
          fence_async_all();
#pragma unroll
          for (int b = 0; b < 5; b++) tma_reduce_add_2d(&mOut, g2_eb * 160 + b * 32, g2_tb * 128 + wg * 64, stg + b * 4096);
          bulk_commit();
          bulk_wait_all();
          if (tid == 0) STAMP(7);
        }
      }
    }
    __syncwarp();
    cluster_arrive();
    cluster_wait();
  } else {
    reg_inc<152>();
    const int ct = tid - 256, w = warp & 3;
    const int cta = blockIdx.x;
    const int c0 = cta * 5;
    const uint32_t cb0 = base + OFF_CB;
    unsigned epoch = 0;
    if (ct == 0) {
      for (int b = 0; b < 2; b++) {
        const uint32_t cb = cb0 + b * CB_BYTES;
        mbar_expect_tx(BAR_CFULL(b), 8192);
        bulk_load(cb + CB_H0, p.ssm_k + (size_t)(c0 + b) * 2048, 4096, BAR_CFULL(b));
      }
      bulk_prefetch(p.ssm_k + (size_t)(c0 + 2) * 2048, 3 * 4096);
      epoch = atomicAdd(&g_ticket, 1u) / NCTA;
      asm volatile("st.shared.u32 [%0], %1;" ::"r"(EPOCH_WORD), "r"(epoch) : "memory");
      mbar_arrive(BAR_EPOCH);
    }
    {
      const int r0 = cta * 16;
#pragma unroll 1
      for (int itx = 0; itx < 5; itx++) {
        const int item = itx * 128 + ct;
        const int half = item / 320, cp = item - half * 320;
        const int s0 = r0 + half * 8;
        uint32_t kk[11], vv[8];
#pragma unroll
        for (int j = 0; j < 11; j++) {
          const int s = s0 - 3 + j;
          kk[j] = (s >= 0) ? ldg32(p.k + (size_t)s * 640 + cp * 2) : 0u;
        }
#pragma unroll
        for (int j = 0; j < 8; j++) vv[j] = ldg32(p.v + (size_t)(s0 + j) * 640 + cp * 2);
        const uint4 sw = *reinterpret_cast<const uint4*>(p.shift_k + cp * 8);
        const uint32_t w0 = __byte_perm(sw.x, sw.z, 0x5410), w1 = __byte_perm(sw.x, sw.z, 0x7632);
        const uint32_t w2 = __byte_perm(sw.y, sw.w, 0x5410), w3 = __byte_perm(sw.y, sw.w, 0x7632);
        uint32_t kv[8];
#pragma unroll
        for (int j = 0; j < 8; j++) {
          uint32_t a = bmul2(kk[j], w3);
          a = badd2(a, bmul2(kk[j + 1], w2));
          a = badd2(a, bmul2(kk[j + 2], w1));
          a = badd2(a, bmul2(kk[j + 3], w0));
          kv[j] = bmul2(a, vv[j]);
        }
        uint4 lo, hi;
        lo.x = __byte_perm(kv[7], kv[6], 0x5410); hi.x = __byte_perm(kv[7], kv[6], 0x7632);
        lo.y = __byte_perm(kv[5], kv[4], 0x5410); hi.y = __byte_perm(kv[5], kv[4], 0x7632);
        lo.z = __byte_perm(kv[3], kv[2], 0x5410); hi.z = __byte_perm(kv[3], kv[2], 0x7632);
        lo.w = __byte_perm(kv[1], kv[0], 0x5410); hi.w = __byte_perm(kv[1], kv[0], 0x7632);
        const int cidx = 255 - (s0 >> 3);
        unsigned char* dst = g_kv + (size_t)(cp * 2) * 4096 + (cidx & 1) * 2048 + (cidx >> 1) * 16;
        *reinterpret_cast<uint4*>(dst) = lo;
        *reinterpret_cast<uint4*>(dst + 4096) = hi;
      }
#pragma unroll
      for (int j = 0; j < 10; j++) {
        const int e = j * 128 + ct;
        const int r = e / 80, cc = e - r * 80;
        *reinterpret_cast<uint4*>(p.out + (size_t)(r0 + r) * 1280 + cc * 8) = make_uint4(0, 0, 0, 0);
      }
      if (ct < 2 * 24) {
        const int b = ct / 24, j = ct % 24;
        const uint32_t cb = cb0 + b * CB_BYTES;
        uint32_t a;
        if (j < 4) a = cb + j * 16;
        else if (j < 16) a = cb + 4160 + (j - 4) * 16;
        else if (j < 20) a = cb + CB_U + 2048 + (j - 16) * 16;
        else a = cb + CB_U + 2112 + 2048 + (j - 20) * 16;
        sts128(a, make_uint4(0, 0, 0, 0));
      }
      fence_async_smem();
      __threadfence();
      bar_sync<4, 128>();
      if (ct == 0) {
        STAMP(8);
        red_release_add(&g_kv_ready, 1u);
        bulk_prefetch(p.q + (size_t)r0 * 640, 16 * 1280);
        wait_ge(&g_kv_ready, (epoch + 1) * NCTA);
        fence_async_all();
        mbar_arrive(BAR_ZERO);
        for (int b = 0; b < 2; b++) {
          const uint32_t cb = cb0 + b * CB_BYTES;
          bulk_load(cb + CB_U, g_kv + (size_t)(c0 + b) * 4096, 2048, BAR_CFULL(b));
          bulk_load(cb + CB_U + 2112, g_kv + (size_t)(c0 + b) * 4096 + 2048, 2048, BAR_CFULL(b));
        }
        STAMP(9);
      }
    }
    const int g = lane >> 2, tig = lane & 3;
    const int x00 = 16 * w - 15 + g + 2 * tig;
    const uint32_t hoff = (x00 & 1) ? (CB_H1 + 2 * (x00 + 1)) : (CB_H0 + 2 * x00);
    const uint32_t part = base + OFF_PART;
    uint32_t pw[4];
#pragma unroll
    for (int jr = 0; jr < 4; jr++) {
      const int j = jr & 1, rh = jr >> 1;
      const int t = 16 * (127 + w) - 32 * tig - 16 * j + 8 * rh + g;
      const int sw = t ^ (((t >> 5) & 3) << 3) ^ (((t >> 5) & 1) << 2);
      pw[jr] = part + w * 8192 + sw * 4;
    }
#pragma unroll 1
    for (int c = 0; c < 5; c++) {
      const int b = c & 1;
      const uint32_t cb = cb0 + b * CB_BYTES;
      mbar_wait(BAR_CFULL(b), (c >> 1) & 1);
      if (ct == 0) STAMP(10 + 2 * c);
      {
        const uint32_t hs = cb + CB_H0 + ct * 32;
        const uint32_t pv = lds32(hs - 4);
        const uint4 v0 = lds128(hs), v1 = lds128(hs + 16);
        uint4 o0, o1;
        o0.x = __byte_perm(pv, v0.x, 0x5432); o0.y = __byte_perm(v0.x, v0.y, 0x5432);
        o0.z = __byte_perm(v0.y, v0.z, 0x5432); o0.w = __byte_perm(v0.z, v0.w, 0x5432);
        o1.x = __byte_perm(v0.w, v1.x, 0x5432); o1.y = __byte_perm(v1.x, v1.y, 0x5432);
        o1.z = __byte_perm(v1.y, v1.z, 0x5432); o1.w = __byte_perm(v1.z, v1.w, 0x5432);
        sts128(cb + CB_H1 + ct * 32, o0);
        sts128(cb + CB_H1 + ct * 32 + 16, o1);
        bar_sync<4, 128>();
      }
      float acc[64];
      const uint32_t hp = cb + hoff;
      const uint64_t descU = mkdesc(cb + CB_U, 2112, 128, 0);
      uint32_t fa[4 * CB], fb[4 * CB];
      conv_load<0>(fa, hp);
      conv_steps<0>(acc, fa, fb, hp, descU);
#pragma unroll
      for (int i = 0; i < 64; i++) asm volatile("" : "+f"(acc[i])::"memory");
      if (ct == 0) STAMP(11 + 2 * c);
#pragma unroll
      for (int G = 0; G < 16; G++) {
#pragma unroll
        for (int jr = 0; jr < 4; jr++) {
          const int j = jr & 1, rh = jr >> 1;
          if (G > 0 || (2 * tig + j >= w)) sts32f(pw[jr] - 512 * G, acc[4 * G + 2 * rh + j]);
        }
      }
      bar_sync<4, 128>();
      const int ch = c0 + c;
      const uint32_t dd = (uint32_t)__bfloat16_as_ushort(p.ssm_D[ch]) * 0x10001u;
#pragma unroll
      for (int h = 0; h < 2; h++) {
        const int mch = ct + h * 128;
        const int t0 = mch * 8;
        const int s0 = t0 ^ (((t0 >> 5) & 3) << 3) ^ (((t0 >> 5) & 1) << 2);
        float4 lo = lds128f(part + s0 * 4), hi = lds128f(part + (s0 ^ 4) * 4);
#pragma unroll
        for (int ww = 1; ww < 4; ww++) {
          if (h > 0 || mch >= 2 * ww) {
            const float4 l2 = lds128f(part + ww * 8192 + s0 * 4), h2 = lds128f(part + ww * 8192 + (s0 ^ 4) * 4);
            lo.x += l2.x; lo.y += l2.y; lo.z += l2.z; lo.w += l2.w;
            hi.x += h2.x; hi.y += h2.y; hi.z += h2.z; hi.w += h2.w;
          }
        }
        const int cidx = 255 - mch;
        const uint4 u = lds128(cb + CB_U + (cidx & 1) * 2112 + (cidx >> 1) * 16);
        uint4 z;
        z.x = badd2(pack_bf16(lo.x, lo.y), bmul2(__byte_perm(u.w, 0, 0x1032), dd));
        z.y = badd2(pack_bf16(lo.z, lo.w), bmul2(__byte_perm(u.z, 0, 0x1032), dd));
        z.z = badd2(pack_bf16(hi.x, hi.y), bmul2(__byte_perm(u.y, 0, 0x1032), dd));
        z.w = badd2(pack_bf16(hi.z, hi.w), bmul2(__byte_perm(u.x, 0, 0x1032), dd));
        *reinterpret_cast<uint4*>(g_z + ((size_t)(mch >> 1) * 640 + ch) * 32 + (mch & 1) * 16) = z;
      }
      if (c == 4) __threadfence();
      bar_sync<4, 128>();
      if (ct == 0 && c + 2 < 5) {
        const int cn = c0 + c + 2;
        mbar_expect_tx(BAR_CFULL(b), 8192);
        bulk_load(cb + CB_H0, p.ssm_k + (size_t)cn * 2048, 4096, BAR_CFULL(b));
        bulk_load(cb + CB_U, g_kv + (size_t)cn * 4096, 2048, BAR_CFULL(b));
        bulk_load(cb + CB_U + 2112, g_kv + (size_t)cn * 4096 + 2048, 2048, BAR_CFULL(b));
      }
    }
    if (ct == 0) {
      STAMP(20);
      red_release_add(&g_z_ready, 1u);
    }
    {
      const int r0 = cta * 16;
      uint32_t qq[5][8];
#pragma unroll
      for (int itx = 0; itx < 5; itx++) {
        const int item = itx * 128 + ct;
        const int half = item / 320, cp = item - half * 320;
#pragma unroll
        for (int j = 0; j < 8; j++) qq[itx][j] = ldg32(p.q + (size_t)(r0 + half * 8 + j) * 640 + cp * 2);
      }
      if (ct == 0) { wait_ge(&g_z_ready, (epoch + 1) * NCTA); STAMP(21); }
      bar_sync<4, 128>();
#pragma unroll
      for (int itx = 0; itx < 5; itx++) {
        const int item = itx * 128 + ct;
        const int half = item / 320, cp = item - half * 320;
        const unsigned char* zs = g_z + ((size_t)cta * 640 + cp * 2) * 32 + half * 16;
        const uint4 z0 = __ldcg(reinterpret_cast<const uint4*>(zs));
        const uint4 z1 = __ldcg(reinterpret_cast<const uint4*>(zs + 32));
        uint32_t zz[8];
        zz[0] = __byte_perm(z0.x, z1.x, 0x5410); zz[1] = __byte_perm(z0.x, z1.x, 0x7632);
        zz[2] = __byte_perm(z0.y, z1.y, 0x5410); zz[3] = __byte_perm(z0.y, z1.y, 0x7632);
        zz[4] = __byte_perm(z0.z, z1.z, 0x5410); zz[5] = __byte_perm(z0.z, z1.z, 0x7632);
        zz[6] = __byte_perm(z0.w, z1.w, 0x5410); zz[7] = __byte_perm(z0.w, z1.w, 0x7632);
#pragma unroll
        for (int j = 0; j < 8; j++)
          *reinterpret_cast<uint32_t*>(p.out + (size_t)(r0 + half * 8 + j) * 1280 + 640 + cp * 2) = bmul2(qq[itx][j], zz[j]);
      }
      if (ct == 0) STAMP(22);
    }
    __syncwarp();
    cluster_arrive();
    cluster_wait();
  }
}

typedef CUresult (*PFN_encodeTiled)(CUtensorMap*, CUtensorMapDataType, cuuint32_t, void*, const cuuint64_t*, const cuuint64_t*,
                                    const cuuint32_t*, const cuuint32_t*, CUtensorMapInterleave, CUtensorMapSwizzle,
                                    CUtensorMapL2promotion, CUtensorMapFloatOOBfill);

static CUtensorMap make_map(PFN_encodeTiled enc, const void* ptr, uint64_t inner, uint64_t outer, uint32_t box_inner, uint32_t box_outer,
                            CUtensorMapSwizzle swz) {
  CUtensorMap m;
  cuuint64_t dims[2] = {inner, outer};
  cuuint64_t strides[1] = {inner * 2};
  cuuint32_t box[2] = {box_inner, box_outer};
  cuuint32_t es[2] = {1, 1};
  enc(&m, CU_TENSOR_MAP_DATA_TYPE_BFLOAT16, 2, const_cast<void*>(ptr), dims, strides, box, es, CU_TENSOR_MAP_INTERLEAVE_NONE, swz,
      CU_TENSOR_MAP_L2_PROMOTION_L2_128B, CU_TENSOR_MAP_FLOAT_OOB_FILL_NONE);
  return m;
}

extern "C" void kernel_launch(void* const* d_in, const int* in_sizes, int n_in, void* d_out, int out_size) {
  static PFN_encodeTiled enc = nullptr;
  if (!enc) {
    void* fp = nullptr;
    cudaDriverEntryPointQueryResult qr;
    cudaGetDriverEntryPoint("cuTensorMapEncodeTiled", &fp, cudaEnableDefault, &qr);
    enc = (PFN_encodeTiled)fp;
    cudaFuncSetAttribute(fused_kernel, cudaFuncAttributeMaxDynamicSharedMemorySize, SMEM_BYTES);
  }
  CUtensorMap mX = make_map(enc, d_in[0], 640, 2048, 64, 64, CU_TENSOR_MAP_SWIZZLE_128B);
  CUtensorMap mCr = make_map(enc, d_in[1], 2048, 2048, 64, 64, CU_TENSOR_MAP_SWIZZLE_128B);
  CUtensorMap mCi = make_map(enc, d_in[2], 2048, 2048, 64, 64, CU_TENSOR_MAP_SWIZZLE_128B);
  CUtensorMap mHr = make_map(enc, d_in[3], 640, 640, 64, 160, CU_TENSOR_MAP_SWIZZLE_128B);
  CUtensorMap mHi = make_map(enc, d_in[4], 640, 640, 64, 160, CU_TENSOR_MAP_SWIZZLE_128B);
  CUtensorMap mOut = make_map(enc, d_out, 1280, 2048, 32, 64, CU_TENSOR_MAP_SWIZZLE_64B);
  Params p;
  p.q = (const __nv_bfloat16*)d_in[5];
  p.k = (const __nv_bfloat16*)d_in[6];
  p.v = (const __nv_bfloat16*)d_in[7];
  p.shift_k = (const __nv_bfloat16*)d_in[8];
  p.ssm_k = (const __nv_bfloat16*)d_in[9];
  p.ssm_D = (const __nv_bfloat16*)d_in[10];
  p.out = (__nv_bfloat16*)d_out;
  fused_kernel<<<NCTA, NTHREADS, SMEM_BYTES>>>(mX, mHr, mHi, mCr, mCi, mOut, p);
}
```

```cpp
#include <cuda_runtime.h>
#include <cuda.h>
#include <cuda_bf16.h>
#include <stdint.h>

#define STAGES 5
#define G_KV 4
#define KVS 0
#define G_F 13
#define XOWN 1
#define NBE 6
#define G_Q 29
#define G_H 26
#define G_T 14
#define MAP 2
#define DI 3
#define R_CONV 184
#define R_GEMM 120
#define R_AUX 88
#define NCTA 128
#define A_BYTES 16384
#define B_BYTES 20480
#define STAGE_BYTES 36864
#define NTHREADS 512

#define OFF_PART   (STAGES * STAGE_BYTES)
#define U_BYTES    4352
#define OFF_UB     (OFF_PART + 16384)
#define OFF_HT     (OFF_UB + 2 * U_BYTES)
#define HC_BYTES   4128
#define HT_BYTES   8256
#define OFF_UA     (OFF_PART + 41728)
#define OFF_BAR    (OFF_PART + 46080)
#define OFF_SK     (OFF_BAR + 256)
#define SMEM_BYTES (OFF_SK + 1280)
#define OFF_HALO   OFF_PART
#define OFF_SLOT(i) (OFF_PART + 1024 + (i) * 4096)
__device__ __forceinline__ uint32_t u_off(int c) { return (c == 0 || c == 3) ? OFF_UA : (c == 2 ? OFF_UB + U_BYTES : OFF_UB); }

__device__ __align__(1024) unsigned char g_u[16 * 2 * 10 * A_BYTES];
__device__ __align__(1024) unsigned char g_t[640 * 4096];
__device__ __align__(1024) __nv_bfloat16 g_z[640 * 2048];
__device__ __align__(128) unsigned g_flag[32 * 32];
__device__ unsigned g_cnt[16 * 32];
__device__ unsigned g_ticket;
#define STAMP(i) do {} while (0)
#define STAMPC(i) do {} while (0)
#define VAL(i, v) do {} while (0)

template<int N> __device__ __forceinline__ void wgmma_ss(float* d, uint64_t a, uint64_t b, int s);
template<int N> __device__ __forceinline__ void wgmma_rs(float* d, uint32_t a0, uint32_t a1, uint32_t a2, uint32_t a3, uint32_t b, int off, int s);
template<> __device__ __forceinline__ void wgmma_ss<160>(float* d, uint64_t descA, uint64_t descB, int scaleD) {
  asm volatile("{\n.reg .pred p;\nsetp.ne.b32 p, %82, 0;\n"
    "wgmma.mma_async.sync.aligned.m64n160k16.f32.bf16.bf16 {%0,%1,%2,%3,%4,%5,%6,%7,%8,%9,%10,%11,%12,%13,%14,%15,%16,%17,%18,%19,%20,%21,%22,%23,%24,%25,%26,%27,%28,%29,%30,%31,%32,%33,%34,%35,%36,%37,%38,%39,%40,%41,%42,%43,%44,%45,%46,%47,%48,%49,%50,%51,%52,%53,%54,%55,%56,%57,%58,%59,%60,%61,%62,%63,%64,%65,%66,%67,%68,%69,%70,%71,%72,%73,%74,%75,%76,%77,%78,%79}, %80, %81, p, 1, 1, 0, 0;\n}\n"
    : "+f"(d[0]),"+f"(d[1]),"+f"(d[2]),"+f"(d[3]),"+f"(d[4]),"+f"(d[5]),"+f"(d[6]),"+f"(d[7]),"+f"(d[8]),"+f"(d[9]),"+f"(d[10]),"+f"(d[11]),"+f"(d[12]),"+f"(d[13]),"+f"(d[14]),"+f"(d[15]),"+f"(d[16]),"+f"(d[17]),"+f"(d[18]),"+f"(d[19]),"+f"(d[20]),"+f"(d[21]),"+f"(d[22]),"+f"(d[23]),"+f"(d[24]),"+f"(d[25]),"+f"(d[26]),"+f"(d[27]),"+f"(d[28]),"+f"(d[29]),"+f"(d[30]),"+f"(d[31]),"+f"(d[32]),"+f"(d[33]),"+f"(d[34]),"+f"(d[35]),"+f"(d[36]),"+f"(d[37]),"+f"(d[38]),"+f"(d[39]),"+f"(d[40]),"+f"(d[41]),"+f"(d[42]),"+f"(d[43]),"+f"(d[44]),"+f"(d[45]),"+f"(d[46]),"+f"(d[47]),"+f"(d[48]),"+f"(d[49]),"+f"(d[50]),"+f"(d[51]),"+f"(d[52]),"+f"(d[53]),"+f"(d[54]),"+f"(d[55]),"+f"(d[56]),"+f"(d[57]),"+f"(d[58]),"+f"(d[59]),"+f"(d[60]),"+f"(d[61]),"+f"(d[62]),"+f"(d[63]),"+f"(d[64]),"+f"(d[65]),"+f"(d[66]),"+f"(d[67]),"+f"(d[68]),"+f"(d[69]),"+f"(d[70]),"+f"(d[71]),"+f"(d[72]),"+f"(d[73]),"+f"(d[74]),"+f"(d[75]),"+f"(d[76]),"+f"(d[77]),"+f"(d[78]),"+f"(d[79])
    : "l"(descA),"l"(descB),"r"(scaleD));
}
__device__ __forceinline__ void wgmma_ss_tb160(float* d, uint64_t descA, uint64_t descB, int scaleD) {
  asm volatile("{\n.reg .pred p;\nsetp.ne.b32 p, %82, 0;\n"
    "wgmma.mma_async.sync.aligned.m64n160k16.f32.bf16.bf16 {%0,%1,%2,%3,%4,%5,%6,%7,%8,%9,%10,%11,%12,%13,%14,%15,%16,%17,%18,%19,%20,%21,%22,%23,%24,%25,%26,%27,%28,%29,%30,%31,%32,%33,%34,%35,%36,%37,%38,%39,%40,%41,%42,%43,%44,%45,%46,%47,%48,%49,%50,%51,%52,%53,%54,%55,%56,%57,%58,%59,%60,%61,%62,%63,%64,%65,%66,%67,%68,%69,%70,%71,%72,%73,%74,%75,%76,%77,%78,%79}, %80, %81, p, 1, 1, 0, 1;\n}\n"
    : "+f"(d[0]),"+f"(d[1]),"+f"(d[2]),"+f"(d[3]),"+f"(d[4]),"+f"(d[5]),"+f"(d[6]),"+f"(d[7]),"+f"(d[8]),"+f"(d[9]),"+f"(d[10]),"+f"(d[11]),"+f"(d[12]),"+f"(d[13]),"+f"(d[14]),"+f"(d[15]),"+f"(d[16]),"+f"(d[17]),"+f"(d[18]),"+f"(d[19]),"+f"(d[20]),"+f"(d[21]),"+f"(d[22]),"+f"(d[23]),"+f"(d[24]),"+f"(d[25]),"+f"(d[26]),"+f"(d[27]),"+f"(d[28]),"+f"(d[29]),"+f"(d[30]),"+f"(d[31]),"+f"(d[32]),"+f"(d[33]),"+f"(d[34]),"+f"(d[35]),"+f"(d[36]),"+f"(d[37]),"+f"(d[38]),"+f"(d[39]),"+f"(d[40]),"+f"(d[41]),"+f"(d[42]),"+f"(d[43]),"+f"(d[44]),"+f"(d[45]),"+f"(d[46]),"+f"(d[47]),"+f"(d[48]),"+f"(d[49]),"+f"(d[50]),"+f"(d[51]),"+f"(d[52]),"+f"(d[53]),"+f"(d[54]),"+f"(d[55]),"+f"(d[56]),"+f"(d[57]),"+f"(d[58]),"+f"(d[59]),"+f"(d[60]),"+f"(d[61]),"+f"(d[62]),"+f"(d[63]),"+f"(d[64]),"+f"(d[65]),"+f"(d[66]),"+f"(d[67]),"+f"(d[68]),"+f"(d[69]),"+f"(d[70]),"+f"(d[71]),"+f"(d[72]),"+f"(d[73]),"+f"(d[74]),"+f"(d[75]),"+f"(d[76]),"+f"(d[77]),"+f"(d[78]),"+f"(d[79])
    : "l"(descA),"l"(descB),"r"(scaleD));
}
template<> __device__ __forceinline__ void wgmma_rs<16>(float* d, uint32_t a0, uint32_t a1, uint32_t a2, uint32_t a3, uint32_t descLo, int off, int scaleD) {
  asm volatile("{\n.reg .pred p;\n.reg .b32 t;\n.reg .b64 d;\nsetp.ne.b32 p, %14, 0;\nadd.u32 t, %12, %13;\nmov.b64 d, {t, 0xC0000010};\n"
    "wgmma.mma_async.sync.aligned.m64n16k16.f32.bf16.bf16 {%0,%1,%2,%3,%4,%5,%6,%7}, {%8,%9,%10,%11}, d, p, 1, 1, 0;\n}\n"
    : "+f"(d[0]),"+f"(d[1]),"+f"(d[2]),"+f"(d[3]),"+f"(d[4]),"+f"(d[5]),"+f"(d[6]),"+f"(d[7])
    : "r"(a0),"r"(a1),"r"(a2),"r"(a3),"r"(descLo),"r"(off),"r"(scaleD));
}
template<> __device__ __forceinline__ void wgmma_rs<32>(float* d, uint32_t a0, uint32_t a1, uint32_t a2, uint32_t a3, uint32_t descLo, int off, int scaleD) {
  asm volatile("{\n.reg .pred p;\n.reg .b32 t;\n.reg .b64 d;\nsetp.ne.b32 p, %22, 0;\nadd.u32 t, %20, %21;\nmov.b64 d, {t, 0xC0000010};\n"
    "wgmma.mma_async.sync.aligned.m64n32k16.f32.bf16.bf16 {%0,%1,%2,%3,%4,%5,%6,%7,%8,%9,%10,%11,%12,%13,%14,%15}, {%16,%17,%18,%19}, d, p, 1, 1, 0;\n}\n"
    : "+f"(d[0]),"+f"(d[1]),"+f"(d[2]),"+f"(d[3]),"+f"(d[4]),"+f"(d[5]),"+f"(d[6]),"+f"(d[7]),"+f"(d[8]),"+f"(d[9]),"+f"(d[10]),"+f"(d[11]),"+f"(d[12]),"+f"(d[13]),"+f"(d[14]),"+f"(d[15])
    : "r"(a0),"r"(a1),"r"(a2),"r"(a3),"r"(descLo),"r"(off),"r"(scaleD));
}
template<> __device__ __forceinline__ void wgmma_rs<48>(float* d, uint32_t a0, uint32_t a1, uint32_t a2, uint32_t a3, uint32_t descLo, int off, int scaleD) {
  asm volatile("{\n.reg .pred p;\n.reg .b32 t;\n.reg .b64 d;\nsetp.ne.b32 p, %30, 0;\nadd.u32 t, %28, %29;\nmov.b64 d, {t, 0xC0000010};\n"
    "wgmma.mma_async.sync.aligned.m64n48k16.f32.bf16.bf16 {%0,%1,%2,%3,%4,%5,%6,%7,%8,%9,%10,%11,%12,%13,%14,%15,%16,%17,%18,%19,%20,%21,%22,%23}, {%24,%25,%26,%27}, d, p, 1, 1, 0;\n}\n"
    : "+f"(d[0]),"+f"(d[1]),"+f"(d[2]),"+f"(d[3]),"+f"(d[4]),"+f"(d[5]),"+f"(d[6]),"+f"(d[7]),"+f"(d[8]),"+f"(d[9]),"+f"(d[10]),"+f"(d[11]),"+f"(d[12]),"+f"(d[13]),"+f"(d[14]),"+f"(d[15]),"+f"(d[16]),"+f"(d[17]),"+f"(d[18]),"+f"(d[19]),"+f"(d[20]),"+f"(d[21]),"+f"(d[22]),"+f"(d[23])
    : "r"(a0),"r"(a1),"r"(a2),"r"(a3),"r"(descLo),"r"(off),"r"(scaleD));
}
template<> __device__ __forceinline__ void wgmma_rs<64>(float* d, uint32_t a0, uint32_t a1, uint32_t a2, uint32_t a3, uint32_t descLo, int off, int scaleD) {
  asm volatile("{\n.reg .pred p;\n.reg .b32 t;\n.reg .b64 d;\nsetp.ne.b32 p, %38, 0;\nadd.u32 t, %36, %37;\nmov.b64 d, {t, 0xC0000010};\n"
    "wgmma.mma_async.sync.aligned.m64n64k16.f32.bf16.bf16 {%0,%1,%2,%3,%4,%5,%6,%7,%8,%9,%10,%11,%12,%13,%14,%15,%16,%17,%18,%19,%20,%21,%22,%23,%24,%25,%26,%27,%28,%29,%30,%31}, {%32,%33,%34,%35}, d, p, 1, 1, 0;\n}\n"
    : "+f"(d[0]),"+f"(d[1]),"+f"(d[2]),"+f"(d[3]),"+f"(d[4]),"+f"(d[5]),"+f"(d[6]),"+f"(d[7]),"+f"(d[8]),"+f"(d[9]),"+f"(d[10]),"+f"(d[11]),"+f"(d[12]),"+f"(d[13]),"+f"(d[14]),"+f"(d[15]),"+f"(d[16]),"+f"(d[17]),"+f"(d[18]),"+f"(d[19]),"+f"(d[20]),"+f"(d[21]),"+f"(d[22]),"+f"(d[23]),"+f"(d[24]),"+f"(d[25]),"+f"(d[26]),"+f"(d[27]),"+f"(d[28]),"+f"(d[29]),"+f"(d[30]),"+f"(d[31])
    : "r"(a0),"r"(a1),"r"(a2),"r"(a3),"r"(descLo),"r"(off),"r"(scaleD));
}
template<> __device__ __forceinline__ void wgmma_rs<80>(float* d, uint32_t a0, uint32_t a1, uint32_t a2, uint32_t a3, uint32_t descLo, int off, int scaleD) {
  asm volatile("{\n.reg .pred p;\n.reg .b32 t;\n.reg .b64 d;\nsetp.ne.b32 p, %46, 0;\nadd.u32 t, %44, %45;\nmov.b64 d, {t, 0xC0000010};\n"
    "wgmma.mma_async.sync.aligned.m64n80k16.f32.bf16.bf16 {%0,%1,%2,%3,%4,%5,%6,%7,%8,%9,%10,%11,%12,%13,%14,%15,%16,%17,%18,%19,%20,%21,%22,%23,%24,%25,%26,%27,%28,%29,%30,%31,%32,%33,%34,%35,%36,%37,%38,%39}, {%40,%41,%42,%43}, d, p, 1, 1, 0;\n}\n"
    : "+f"(d[0]),"+f"(d[1]),"+f"(d[2]),"+f"(d[3]),"+f"(d[4]),"+f"(d[5]),"+f"(d[6]),"+f"(d[7]),"+f"(d[8]),"+f"(d[9]),"+f"(d[10]),"+f"(d[11]),"+f"(d[12]),"+f"(d[13]),"+f"(d[14]),"+f"(d[15]),"+f"(d[16]),"+f"(d[17]),"+f"(d[18]),"+f"(d[19]),"+f"(d[20]),"+f"(d[21]),"+f"(d[22]),"+f"(d[23]),"+f"(d[24]),"+f"(d[25]),"+f"(d[26]),"+f"(d[27]),"+f"(d[28]),"+f"(d[29]),"+f"(d[30]),"+f"(d[31]),"+f"(d[32]),"+f"(d[33]),"+f"(d[34]),"+f"(d[35]),"+f"(d[36]),"+f"(d[37]),"+f"(d[38]),"+f"(d[39])
    : "r"(a0),"r"(a1),"r"(a2),"r"(a3),"r"(descLo),"r"(off),"r"(scaleD));
}
template<> __device__ __forceinline__ void wgmma_rs<96>(float* d, uint32_t a0, uint32_t a1, uint32_t a2, uint32_t a3, uint32_t descLo, int off, int scaleD) {
  asm volatile("{\n.reg .pred p;\n.reg .b32 t;\n.reg .b64 d;\nsetp.ne.b32 p, %54, 0;\nadd.u32 t, %52, %53;\nmov.b64 d, {t, 0xC0000010};\n"
    "wgmma.mma_async.sync.aligned.m64n96k16.f32.bf16.bf16 {%0,%1,%2,%3,%4,%5,%6,%7,%8,%9,%10,%11,%12,%13,%14,%15,%16,%17,%18,%19,%20,%21,%22,%23,%24,%25,%26,%27,%28,%29,%30,%31,%32,%33,%34,%35,%36,%37,%38,%39,%40,%41,%42,%43,%44,%45,%46,%47}, {%48,%49,%50,%51}, d, p, 1, 1, 0;\n}\n"
    : "+f"(d[0]),"+f"(d[1]),"+f"(d[2]),"+f"(d[3]),"+f"(d[4]),"+f"(d[5]),"+f"(d[6]),"+f"(d[7]),"+f"(d[8]),"+f"(d[9]),"+f"(d[10]),"+f"(d[11]),"+f"(d[12]),"+f"(d[13]),"+f"(d[14]),"+f"(d[15]),"+f"(d[16]),"+f"(d[17]),"+f"(d[18]),"+f"(d[19]),"+f"(d[20]),"+f"(d[21]),"+f"(d[22]),"+f"(d[23]),"+f"(d[24]),"+f"(d[25]),"+f"(d[26]),"+f"(d[27]),"+f"(d[28]),"+f"(d[29]),"+f"(d[30]),"+f"(d[31]),"+f"(d[32]),"+f"(d[33]),"+f"(d[34]),"+f"(d[35]),"+f"(d[36]),"+f"(d[37]),"+f"(d[38]),"+f"(d[39]),"+f"(d[40]),"+f"(d[41]),"+f"(d[42]),"+f"(d[43]),"+f"(d[44]),"+f"(d[45]),"+f"(d[46]),"+f"(d[47])
    : "r"(a0),"r"(a1),"r"(a2),"r"(a3),"r"(descLo),"r"(off),"r"(scaleD));
}
template<> __device__ __forceinline__ void wgmma_rs<112>(float* d, uint32_t a0, uint32_t a1, uint32_t a2, uint32_t a3, uint32_t descLo, int off, int scaleD) {
  asm volatile("{\n.reg .pred p;\n.reg .b32 t;\n.reg .b64 d;\nsetp.ne.b32 p, %62, 0;\nadd.u32 t, %60, %61;\nmov.b64 d, {t, 0xC0000010};\n"
    "wgmma.mma_async.sync.aligned.m64n112k16.f32.bf16.bf16 {%0,%1,%2,%3,%4,%5,%6,%7,%8,%9,%10,%11,%12,%13,%14,%15,%16,%17,%18,%19,%20,%21,%22,%23,%24,%25,%26,%27,%28,%29,%30,%31,%32,%33,%34,%35,%36,%37,%38,%39,%40,%41,%42,%43,%44,%45,%46,%47,%48,%49,%50,%51,%52,%53,%54,%55}, {%56,%57,%58,%59}, d, p, 1, 1, 0;\n}\n"
    : "+f"(d[0]),"+f"(d[1]),"+f"(d[2]),"+f"(d[3]),"+f"(d[4]),"+f"(d[5]),"+f"(d[6]),"+f"(d[7]),"+f"(d[8]),"+f"(d[9]),"+f"(d[10]),"+f"(d[11]),"+f"(d[12]),"+f"(d[13]),"+f"(d[14]),"+f"(d[15]),"+f"(d[16]),"+f"(d[17]),"+f"(d[18]),"+f"(d[19]),"+f"(d[20]),"+f"(d[21]),"+f"(d[22]),"+f"(d[23]),"+f"(d[24]),"+f"(d[25]),"+f"(d[26]),"+f"(d[27]),"+f"(d[28]),"+f"(d[29]),"+f"(d[30]),"+f"(d[31]),"+f"(d[32]),"+f"(d[33]),"+f"(d[34]),"+f"(d[35]),"+f"(d[36]),"+f"(d[37]),"+f"(d[38]),"+f"(d[39]),"+f"(d[40]),"+f"(d[41]),"+f"(d[42]),"+f"(d[43]),"+f"(d[44]),"+f"(d[45]),"+f"(d[46]),"+f"(d[47]),"+f"(d[48]),"+f"(d[49]),"+f"(d[50]),"+f"(d[51]),"+f"(d[52]),"+f"(d[53]),"+f"(d[54]),"+f"(d[55])
    : "r"(a0),"r"(a1),"r"(a2),"r"(a3),"r"(descLo),"r"(off),"r"(scaleD));
}
template<> __device__ __forceinline__ void wgmma_rs<128>(float* d, uint32_t a0, uint32_t a1, uint32_t a2, uint32_t a3, uint32_t descLo, int off, int scaleD) {
  asm volatile("{\n.reg .pred p;\n.reg .b32 t;\n.reg .b64 d;\nsetp.ne.b32 p, %70, 0;\nadd.u32 t, %68, %69;\nmov.b64 d, {t, 0xC0000010};\n"
    "wgmma.mma_async.sync.aligned.m64n128k16.f32.bf16.bf16 {%0,%1,%2,%3,%4,%5,%6,%7,%8,%9,%10,%11,%12,%13,%14,%15,%16,%17,%18,%19,%20,%21,%22,%23,%24,%25,%26,%27,%28,%29,%30,%31,%32,%33,%34,%35,%36,%37,%38,%39,%40,%41,%42,%43,%44,%45,%46,%47,%48,%49,%50,%51,%52,%53,%54,%55,%56,%57,%58,%59,%60,%61,%62,%63}, {%64,%65,%66,%67}, d, p, 1, 1, 0;\n}\n"
    : "+f"(d[0]),"+f"(d[1]),"+f"(d[2]),"+f"(d[3]),"+f"(d[4]),"+f"(d[5]),"+f"(d[6]),"+f"(d[7]),"+f"(d[8]),"+f"(d[9]),"+f"(d[10]),"+f"(d[11]),"+f"(d[12]),"+f"(d[13]),"+f"(d[14]),"+f"(d[15]),"+f"(d[16]),"+f"(d[17]),"+f"(d[18]),"+f"(d[19]),"+f"(d[20]),"+f"(d[21]),"+f"(d[22]),"+f"(d[23]),"+f"(d[24]),"+f"(d[25]),"+f"(d[26]),"+f"(d[27]),"+f"(d[28]),"+f"(d[29]),"+f"(d[30]),"+f"(d[31]),"+f"(d[32]),"+f"(d[33]),"+f"(d[34]),"+f"(d[35]),"+f"(d[36]),"+f"(d[37]),"+f"(d[38]),"+f"(d[39]),"+f"(d[40]),"+f"(d[41]),"+f"(d[42]),"+f"(d[43]),"+f"(d[44]),"+f"(d[45]),"+f"(d[46]),"+f"(d[47]),"+f"(d[48]),"+f"(d[49]),"+f"(d[50]),"+f"(d[51]),"+f"(d[52]),"+f"(d[53]),"+f"(d[54]),"+f"(d[55]),"+f"(d[56]),"+f"(d[57]),"+f"(d[58]),"+f"(d[59]),"+f"(d[60]),"+f"(d[61]),"+f"(d[62]),"+f"(d[63])
    : "r"(a0),"r"(a1),"r"(a2),"r"(a3),"r"(descLo),"r"(off),"r"(scaleD));
}

__device__ __forceinline__ uint32_t smem_u32(const void* p) { return (uint32_t)__cvta_generic_to_shared(p); }
__device__ __forceinline__ uint64_t mkdesc(uint32_t addr, uint32_t lbo, uint32_t sbo, int swz) {
  return (uint64_t)((addr & 0x3FFFF) >> 4) | ((uint64_t)(lbo >> 4) << 16) | ((uint64_t)(sbo >> 4) << 32) | ((uint64_t)swz << 62);
}
__device__ __forceinline__ unsigned long long gtime() { unsigned long long t; asm volatile("mov.u64 %0, %%globaltimer;" : "=l"(t)); return t; }
__device__ __forceinline__ void mbar_init(uint32_t bar, int count) { asm volatile("mbarrier.init.shared::cta.b64 [%0], %1;" ::"r"(bar), "r"(count) : "memory"); }
__device__ __forceinline__ void mbar_expect_tx(uint32_t bar, uint32_t bytes) { asm volatile("mbarrier.arrive.expect_tx.shared::cta.b64 _, [%0], %1;" ::"r"(bar), "r"(bytes) : "memory"); }
__device__ __forceinline__ void mbar_arrive(uint32_t bar) { asm volatile("mbarrier.arrive.shared::cta.b64 _, [%0];" ::"r"(bar) : "memory"); }
__device__ __forceinline__ void mbar_arrive_cta(uint32_t bar, uint32_t cta) {
  asm volatile("{\n.reg .b32 ra;\nmapa.shared::cluster.u32 ra, %0, %1;\nmbarrier.arrive.shared::cluster.b64 _, [ra];\n}\n" ::"r"(bar), "r"(cta) : "memory");
}
__device__ __forceinline__ void mbar_wait(uint32_t bar, uint32_t parity) {
  uint32_t ok;
  int tries = 0;
#pragma unroll 1
  do {
    asm volatile("{\n.reg .pred p;\nmbarrier.try_wait.parity.shared::cta.b64 p, [%1], %2;\nselp.u32 %0, 1, 0, p;\n}\n" : "=r"(ok) : "r"(bar), "r"(parity) : "memory");
  } while (!ok && ++tries < (1 << 17));
}
#define SLP 100
__device__ __forceinline__ void mbar_wait_slow(uint32_t bar, uint32_t parity) {
  uint32_t ok;
  int tries = 0;
#pragma unroll 1
  do {
    asm volatile("{\n.reg .pred p;\nmbarrier.test_wait.parity.shared::cta.b64 p, [%1], %2;\nselp.u32 %0, 1, 0, p;\n}\n" : "=r"(ok) : "r"(bar), "r"(parity) : "memory");
    if (!ok) __nanosleep(SLP);
  } while (!ok && ++tries < (1 << 17));
}
__device__ __forceinline__ uint32_t mbar_test(uint32_t bar, uint32_t parity) {
  uint32_t ok;
  asm volatile("{\n.reg .pred p;\nmbarrier.test_wait.parity.shared::cta.b64 p, [%1], %2;\nselp.u32 %0, 1, 0, p;\n}\n" : "=r"(ok) : "r"(bar), "r"(parity) : "memory");
  return ok;
}
__device__ __forceinline__ void tma_load_2d(uint32_t dst, const CUtensorMap* map, int c0, int c1, uint32_t bar) {
  asm volatile("cp.async.bulk.tensor.2d.shared::cluster.global.mbarrier::complete_tx::bytes [%0], [%1, {%3, %4}], [%2];"
               ::"r"(dst), "l"((uint64_t)map), "r"(bar), "r"(c0), "r"(c1) : "memory");
}
__device__ __forceinline__ void tma_load_2d_mc(uint32_t dst, const CUtensorMap* map, int c0, int c1, uint32_t bar, uint16_t mask) {
  asm volatile("cp.async.bulk.tensor.2d.shared::cluster.global.mbarrier::complete_tx::bytes.multicast::cluster [%0], [%1, {%3, %4}], [%2], %5;"
               ::"r"(dst), "l"((uint64_t)map), "r"(bar), "r"(c0), "r"(c1), "h"(mask) : "memory");
}
__device__ __forceinline__ void tma_prefetch_2d(const CUtensorMap* map, int c0, int c1) {
  asm volatile("cp.async.bulk.prefetch.tensor.2d.L2.global [%0, {%1, %2}];" ::"l"((uint64_t)map), "r"(c0), "r"(c1) : "memory");
}
__device__ __forceinline__ void bulk_load(uint32_t dst, const void* src, uint32_t bytes, uint32_t bar) {
  asm volatile("cp.async.bulk.shared::cluster.global.mbarrier::complete_tx::bytes [%0], [%1], %2, [%3];"
               ::"r"(dst), "l"((uint64_t)src), "r"(bytes), "r"(bar) : "memory");
}
__device__ __forceinline__ void bulk_store(void* dst, uint32_t src, uint32_t bytes) {
  asm volatile("cp.async.bulk.global.shared::cta.bulk_group [%0], [%1], %2;" ::"l"((uint64_t)dst), "r"(src), "r"(bytes) : "memory");
}
__device__ __forceinline__ void bulk_prefetch(const void* src, uint32_t bytes) {
  asm volatile("cp.async.bulk.prefetch.L2.global [%0], %1;" ::"l"((uint64_t)src), "r"(bytes) : "memory");
}
__device__ __forceinline__ void tma_reduce_add_2d(const CUtensorMap* map, int c0, int c1, uint32_t src) {
  asm volatile("cp.reduce.async.bulk.tensor.2d.global.shared::cta.add.tile.bulk_group [%0, {%1, %2}], [%3];"
               ::"l"((uint64_t)map), "r"(c0), "r"(c1), "r"(src) : "memory");
}
__device__ __forceinline__ void bulk_commit() { asm volatile("cp.async.bulk.commit_group;" ::: "memory"); }
__device__ __forceinline__ void bulk_wait_all() { asm volatile("cp.async.bulk.wait_group 0;" ::: "memory"); }
__device__ __forceinline__ void bulk_wait_read() { asm volatile("cp.async.bulk.wait_group.read 0;" ::: "memory"); }
__device__ __forceinline__ void fence_async_smem() { asm volatile("fence.proxy.async.shared::cta;" ::: "memory"); }
__device__ __forceinline__ void fence_async_all() { asm volatile("fence.proxy.async.global;" ::: "memory"); }
__device__ __forceinline__ void cluster_arrive() { asm volatile("barrier.cluster.arrive.relaxed.aligned;" ::: "memory"); }
__device__ __forceinline__ void cluster_wait() { asm volatile("barrier.cluster.wait.aligned;" ::: "memory"); }
__device__ __forceinline__ void prefetch_map(const CUtensorMap* m) { asm volatile("prefetch.tensormap [%0];" ::"l"((uint64_t)m) : "memory"); }
__device__ __forceinline__ uint32_t cluster_rank() { uint32_t r; asm volatile("mov.u32 %0, %%cluster_ctarank;" : "=r"(r)); return r; }
__device__ __forceinline__ uint32_t smid() { uint32_t r; asm volatile("mov.u32 %0, %%smid;" : "=r"(r)); return r; }
__device__ __forceinline__ bool elect_one() {
  uint32_t p;
  asm volatile("{\n.reg .pred P;\nelect.sync _|P, 0xffffffff;\nselp.b32 %0, 1, 0, P;\n}\n" : "=r"(p));
  return p != 0;
}
__device__ __forceinline__ void wg_fence() { asm volatile("wgmma.fence.sync.aligned;" ::: "memory"); }
__device__ __forceinline__ void wg_commit() { asm volatile("wgmma.commit_group.sync.aligned;" ::: "memory"); }
template <int N> __device__ __forceinline__ void wg_wait() { asm volatile("wgmma.wait_group.sync.aligned %0;" ::"n"(N) : "memory"); }
template <int ID, int N> __device__ __forceinline__ void bar_sync() { asm volatile("bar.sync %0, %1;" ::"n"(ID), "n"(N) : "memory"); }
template <int ID, int N> __device__ __forceinline__ void bar_arrive() { asm volatile("bar.arrive %0, %1;" ::"n"(ID), "n"(N) : "memory"); }
template <int R> __device__ __forceinline__ void reg_inc() { asm volatile("setmaxnreg.inc.sync.aligned.u32 %0;" ::"n"(R)); }
template <int R> __device__ __forceinline__ void reg_dec() { asm volatile("setmaxnreg.dec.sync.aligned.u32 %0;" ::"n"(R)); }
__device__ __forceinline__ unsigned ld_acquire(const unsigned* p) { unsigned v; asm volatile("ld.acquire.gpu.global.u32 %0, [%1];" : "=r"(v) : "l"(p) : "memory"); return v; }
__device__ __forceinline__ void st_release(unsigned* p, unsigned v) { asm volatile("st.release.gpu.global.u32 [%0], %1;" ::"l"(p), "r"(v) : "memory"); }
__device__ __forceinline__ void red_release_add(unsigned* p, unsigned v) { asm volatile("red.release.gpu.global.add.u32 [%0], %1;" ::"l"(p), "r"(v) : "memory"); }
__device__ __forceinline__ void wait_ge(const unsigned* p, unsigned target) {
  int tries = 0;
#pragma unroll 1
  while ((int)(ld_acquire(p) - target) < 0) {
    __nanosleep(40);
    if (++tries > (1 << 18)) break;
  }
}
__device__ __forceinline__ uint32_t lds32(uint32_t a) { uint32_t v; asm volatile("ld.shared.u32 %0, [%1];" : "=r"(v) : "r"(a) : "memory"); return v; }
__device__ __forceinline__ uint4 lds128(uint32_t a) { uint4 v; asm volatile("ld.shared.v4.u32 {%0,%1,%2,%3}, [%4];" : "=r"(v.x), "=r"(v.y), "=r"(v.z), "=r"(v.w) : "r"(a) : "memory"); return v; }
__device__ __forceinline__ float4 lds128f(uint32_t a) { float4 v; asm volatile("ld.shared.v4.f32 {%0,%1,%2,%3}, [%4];" : "=f"(v.x), "=f"(v.y), "=f"(v.z), "=f"(v.w) : "r"(a) : "memory"); return v; }
__device__ __forceinline__ void sts32f(uint32_t a, float v) { asm volatile("st.shared.f32 [%0], %1;" ::"r"(a), "f"(v) : "memory"); }
__device__ __forceinline__ void sts128(uint32_t a, uint4 v) { asm volatile("st.shared.v4.u32 [%0], {%1,%2,%3,%4};" ::"r"(a), "r"(v.x), "r"(v.y), "r"(v.z), "r"(v.w) : "memory"); }
__device__ __forceinline__ void stmatrix_x4(uint32_t a, uint32_t r0, uint32_t r1, uint32_t r2, uint32_t r3) {
  asm volatile("stmatrix.sync.aligned.m8n8.x4.shared.b16 [%0], {%1,%2,%3,%4};" ::"r"(a), "r"(r0), "r"(r1), "r"(r2), "r"(r3) : "memory");
}
__device__ __forceinline__ void stmatrix_x4_trans(uint32_t a, uint32_t r0, uint32_t r1, uint32_t r2, uint32_t r3) {
  asm volatile("stmatrix.sync.aligned.m8n8.x4.trans.shared.b16 [%0], {%1,%2,%3,%4};" ::"r"(a), "r"(r0), "r"(r1), "r"(r2), "r"(r3) : "memory");
}
__device__ __forceinline__ uint32_t pack_bf16(float lo, float hi) {
  uint32_t r; asm("cvt.rn.bf16x2.f32 %0, %1, %2;" : "=r"(r) : "f"(hi), "f"(lo)); return r;
}
__device__ __forceinline__ uint32_t bmul2(uint32_t a, uint32_t b) { uint32_t r; asm("mul.rn.bf16x2 %0, %1, %2;" : "=r"(r) : "r"(a), "r"(b)); return r; }
__device__ __forceinline__ uint32_t badd2(uint32_t a, uint32_t b) { uint32_t r; asm("add.rn.bf16x2 %0, %1, %2;" : "=r"(r) : "r"(a), "r"(b)); return r; }
__device__ __forceinline__ uint32_t ldg32(const void* p) { uint32_t v; asm volatile("ld.global.nc.u32 %0, [%1];" : "=r"(v) : "l"(p)); return v; }

__device__ __forceinline__ void tma_load_3d_mc(uint32_t dst, const CUtensorMap* map, int c0, int c1, int c2, uint32_t bar, uint16_t mask) {
  asm volatile("cp.async.bulk.tensor.3d.shared::cluster.global.mbarrier::complete_tx::bytes.multicast::cluster [%0], [%1, {%3, %4, %5}], [%2], %6;"
               ::"r"(dst), "l"((uint64_t)map), "r"(bar), "r"(c0), "r"(c1), "r"(c2), "h"(mask) : "memory");
}
__device__ __forceinline__ void tma_load_3d(uint32_t dst, const CUtensorMap* map, int c0, int c1, int c2, uint32_t bar) {
  asm volatile("cp.async.bulk.tensor.3d.shared::cluster.global.mbarrier::complete_tx::bytes [%0], [%1, {%3, %4, %5}], [%2];"
               ::"r"(dst), "l"((uint64_t)map), "r"(bar), "r"(c0), "r"(c1), "r"(c2) : "memory");
}
__device__ __forceinline__ void tma_store_2d(const CUtensorMap* map, int c0, int c1, uint32_t src) {
  asm volatile("cp.async.bulk.tensor.2d.global.shared::cta.tile.bulk_group [%0, {%1, %2}], [%3];"
               ::"l"((uint64_t)map), "r"(c0), "r"(c1), "r"(src) : "memory");
}
__device__ __forceinline__ void red_relaxed_add(unsigned* p, unsigned v) { asm volatile("red.relaxed.gpu.global.add.u32 [%0], %1;" ::"l"(p), "r"(v) : "memory"); }
__device__ __forceinline__ uint32_t mapa(uint32_t a, uint32_t cta) { uint32_t r; asm("mapa.shared::cluster.u32 %0, %1, %2;" : "=r"(r) : "r"(a), "r"(cta)); return r; }
__device__ __forceinline__ void st_async128(uint32_t a, uint4 v, uint32_t bar) {
  asm volatile("st.async.weak.shared::cluster.mbarrier::complete_tx::bytes.v4.b32 [%0], {%1,%2,%3,%4}, [%5];"
               ::"r"(a), "r"(v.x), "r"(v.y), "r"(v.z), "r"(v.w), "r"(bar) : "memory");
}
__device__ __forceinline__ void st_relaxed(unsigned* p, unsigned v) { asm volatile("st.relaxed.gpu.global.u32 [%0], %1;" ::"l"(p), "r"(v) : "memory"); }
__device__ __forceinline__ uint4 ldg128(const void* p) {
  uint4 v; asm volatile("ld.global.nc.L1::no_allocate.v4.u32 {%0,%1,%2,%3}, [%4];" : "=r"(v.x), "=r"(v.y), "=r"(v.z), "=r"(v.w) : "l"(p)); return v;
}
__device__ __forceinline__ uint32_t lds16(uint32_t a) { uint16_t v; asm volatile("ld.shared.u16 %0, [%1];" : "=h"(v) : "r"(a) : "memory"); return v; }
__device__ __forceinline__ float bf_lo(uint32_t v) { return __uint_as_float(v << 16); }
__device__ __forceinline__ float bf_hi(uint32_t v) { return __uint_as_float(v & 0xffff0000u); }

#define BAR_FULL(s)  (bars + 8 * (s))
#define BAR_EMPTY(s) (bars + 8 * (5 + (s)))
#define BAR_KV(i)    (bars + 8 * (10 + (i)))
#define BAR_XFULL(g) (bars + 8 * (15 + (g)))
#define BAR_U(c)     (bars + 8 * (17 + (c)))
#define BAR_TAB(c)   (bars + 8 * (22 + (c)))
#define BAR_XFREE    (bars + 8 * 27)
#define BAR_EPOCH    (bars + 8 * 28)
#define BAR_EPI(g)   (bars + 8 * (29 + (g)))
#define EPOCH_WORD   (bars + 8 * 31)
#define NB_G0 2
#define NB_G1 3
#define NB_AUX 4
#define NB_PRE 5
#define NB_PUB 6
#define NB_T0 7
#define NB_PFULL 8
#define NB_PFREE 9

__device__ __forceinline__ void frag_load(uint32_t (&f)[16], uint32_t hp) {
#pragma unroll
  for (int j = 0; j < 4; j++) {
    f[4 * j + 0] = lds32(hp + 32 * j);
    f[4 * j + 1] = lds32(hp + 32 * j + 256);
    f[4 * j + 2] = lds32(hp + 32 * j + 16);
    f[4 * j + 3] = lds32(hp + 32 * j + 272);
  }
}
template <int B>
__device__ __forceinline__ void conv_batch(float* acc, uint32_t (&f)[16], uint32_t hp, uint32_t desc) {
  frag_load(f, hp + 512 * B);
  wg_fence();
#pragma unroll
  for (int j = 0; j < 4; j++) wgmma_rs<128 - 16 * B>(acc, f[4 * j], f[4 * j + 1], f[4 * j + 2], f[4 * j + 3], desc, 32 * B + 2 * j, B >= 2 || j != 0);
  wg_commit();
}
template <int N>
__device__ __forceinline__ void conv_rename(float* acc) {
#pragma unroll
  for (int i = 0; i < N / 2; i++) { float t; asm volatile("mov.b32 %0, %1;" : "=f"(t) : "f"(acc[i]) : "memory"); acc[i] = t; }
}
template <int G0, int G1>
__device__ __forceinline__ void conv_dump(const float* X, const float* Y, const uint32_t (&pw)[2], bool late) {
#pragma unroll
  for (int G = G0; G < G1; G++) {
#pragma unroll
    for (int j = 0; j < 2; j++) {
      float v = X[4 * G + j];
      if (G < 15) v += X[4 * G + 6 + j];
      if (G < 13) v += Y[4 * G + j] + Y[4 * G + 6 + j];
      else if (G < 14) v += Y[4 * G + j];
      if (G != 0 || !late) sts32f(pw[j] - 512 * G, v);
    }
  }
}
template <int B>
__device__ __forceinline__ void conv_round(float* X, float* Y, uint32_t (&fx)[16], uint32_t (&fy)[16], uint32_t hp, uint32_t desc,
                                           const uint32_t (&pw)[2], bool late) {
  wg_wait<B < 8 ? 1 : 0>();
  conv_rename<144 - 16 * B>((B & 1) ? X : Y);
  if constexpr (B < 7) conv_batch<B + 1>((B & 1) ? X : Y, (B & 1) ? fx : fy, hp, desc);
  if constexpr (B == DI) bar_sync<NB_PFREE, 224>();
  if constexpr (B >= DI) conv_dump<16 - 2 * B, B == DI ? 16 : 18 - 2 * B>(X, Y, pw, late);
}
__device__ __forceinline__ void conv_channel(uint32_t hp, uint32_t desc, const uint32_t (&pw)[2], bool late) {
  float X[64], Y[56];
  uint32_t fx[16], fy[16];
  conv_batch<0>(X, fx, hp, desc);
  conv_batch<1>(Y, fy, hp, desc);
  conv_round<1>(X, Y, fx, fy, hp, desc, pw, late);
  conv_round<2>(X, Y, fx, fy, hp, desc, pw, late);
  conv_round<3>(X, Y, fx, fy, hp, desc, pw, late);
  conv_round<4>(X, Y, fx, fy, hp, desc, pw, late);
  conv_round<5>(X, Y, fx, fy, hp, desc, pw, late);
  conv_round<6>(X, Y, fx, fy, hp, desc, pw, late);
  conv_round<7>(X, Y, fx, fy, hp, desc, pw, late);
  conv_round<8>(X, Y, fx, fy, hp, desc, pw, late);
}

#define KERNEL_END() do { cluster_arrive(); cluster_wait(); } while (0)

struct Params {
  const __nv_bfloat16 *hr, *hi, *q, *shift_k, *ssm_k, *ssm_D;
  __nv_bfloat16* out;
};

__device__ __forceinline__ void fin_phase(const Params& p, uint32_t bars, int i, int lane, int cta) {
  const int c = (cta & 3) * 160 + i * 32 + (lane & 3) * 8, t0 = (cta >> 2) * 64 + (lane >> 2) * 8;
  const int cidx = 255 - (t0 >> 3);
  const __nv_bfloat16* zs = g_z + (size_t)c * 2048 + (cidx ^ ((cidx >> 3) & 1)) * 8;
  const __nv_bfloat16* qs = p.q + (size_t)t0 * 640 + c;
  uint4* dst = reinterpret_cast<uint4*>(p.out + (size_t)t0 * 1280 + 640 + c);
  const unsigned* cnt = &g_cnt[(8 + (i & 4) + (cta & 3)) * 32];
  const unsigned target = (lds32(EPOCH_WORD) + 1) * 32;
  if (i < 4) {
    wait_ge(cnt, target);
    mbar_wait_slow(BAR_EPOCH, 1);
    if (i == 0 && lane == 0) STAMP(44);
  }
  uint4 q[8];
  uint32_t z[8][4];
#pragma unroll
  for (int j = 0; j < 8; j++) q[j] = ldg128(qs + j * 640);
  if (i == 4) wait_ge(cnt, target);
  if (i == 4 && lane == 0) STAMP(43);
  asm volatile("ld.relaxed.gpu.global.v4.u32 {%0,%1,%2,%3}, [%32+0];\n"
               "ld.relaxed.gpu.global.v4.u32 {%4,%5,%6,%7}, [%32+4096];\n"
               "ld.relaxed.gpu.global.v4.u32 {%8,%9,%10,%11}, [%32+8192];\n"
               "ld.relaxed.gpu.global.v4.u32 {%12,%13,%14,%15}, [%32+12288];\n"
               "ld.relaxed.gpu.global.v4.u32 {%16,%17,%18,%19}, [%32+16384];\n"
               "ld.relaxed.gpu.global.v4.u32 {%20,%21,%22,%23}, [%32+20480];\n"
               "ld.relaxed.gpu.global.v4.u32 {%24,%25,%26,%27}, [%32+24576];\n"
               "ld.relaxed.gpu.global.v4.u32 {%28,%29,%30,%31}, [%32+28672];\n"
               : "=r"(z[0][0]), "=r"(z[0][1]), "=r"(z[0][2]), "=r"(z[0][3]), "=r"(z[1][0]), "=r"(z[1][1]), "=r"(z[1][2]), "=r"(z[1][3]), "=r"(z[2][0]), "=r"(z[2][1]), "=r"(z[2][2]), "=r"(z[2][3]), "=r"(z[3][0]), "=r"(z[3][1]), "=r"(z[3][2]), "=r"(z[3][3]), "=r"(z[4][0]), "=r"(z[4][1]), "=r"(z[4][2]), "=r"(z[4][3]), "=r"(z[5][0]), "=r"(z[5][1]), "=r"(z[5][2]), "=r"(z[5][3]), "=r"(z[6][0]), "=r"(z[6][1]), "=r"(z[6][2]), "=r"(z[6][3]), "=r"(z[7][0]), "=r"(z[7][1]), "=r"(z[7][2]), "=r"(z[7][3])
               : "l"(zs) : "memory");
  __syncwarp();
#pragma unroll
  for (int j = 0; j < 8; j++) {
    const uint32_t sel = (j & 1) ? 0x7632 : 0x5410;
    dst[j * 160] = make_uint4(bmul2(q[j].x, __byte_perm(z[0][j >> 1], z[1][j >> 1], sel)), bmul2(q[j].y, __byte_perm(z[2][j >> 1], z[3][j >> 1], sel)),
                              bmul2(q[j].z, __byte_perm(z[4][j >> 1], z[5][j >> 1], sel)), bmul2(q[j].w, __byte_perm(z[6][j >> 1], z[7][j >> 1], sel)));
  }
  if (i == 3 && lane == 0) STAMP(21);
  if (i == 4 && lane == 0) STAMP(22);
}

__device__ __forceinline__ void pre_phase(uint32_t base, uint32_t bars, int wt, int cta) {
  const int rg = wt >> 4, cp = wt & 15;
  const int uk = (7 - rg) ^ (((cta >> 2) & 1) ^ 1);
  uint32_t sk = base + OFF_SK + cp * 16;
  uint32_t ak = base + OFF_SLOT(9) + rg * 512 + cp * 4, av = base + OFF_SLOT(0) + rg * 512 + cp * 4;
  uint32_t ah = rg ? ak - 192 : base + OFF_HALO + cp * 4;
  const int hstep = rg ? -4096 : 192;
  const uint32_t ob = base + cp * 256 + ((uk ^ ((2 * cp) & 7)) << 4);
#pragma unroll 1
  for (int i = 0; i < 5; i++) {
    mbar_wait_slow(BAR_KV(i), 0);
    if (wt == 0 && i == 0) STAMP(32);
    if (wt == 0 && i == 4) STAMP(46);
    const uint4 sw = lds128(sk);
    uint32_t kk[11], kv[8];
#pragma unroll
    for (int j = 0; j < 3; j++) kk[j] = lds32(ah + j * 64);
#pragma unroll
    for (int j = 0; j < 8; j++) kk[3 + j] = lds32(ak + j * 64);
#pragma unroll
    for (int j = 0; j < 8; j++) kv[j] = lds32(av + j * 64);
    const uint32_t w0 = __byte_perm(sw.x, sw.z, 0x5410), w1 = __byte_perm(sw.x, sw.z, 0x7632);
    const uint32_t w2 = __byte_perm(sw.y, sw.w, 0x5410), w3 = __byte_perm(sw.y, sw.w, 0x7632);
#pragma unroll
    for (int j = 0; j < 8; j++) {
      uint32_t a = bmul2(kk[j], w3);
      a = badd2(a, bmul2(kk[j + 1], w2));
      a = badd2(a, bmul2(kk[j + 2], w1));
      a = badd2(a, bmul2(kk[j + 3], w0));
      kv[j] = bmul2(a, kv[j]);
    }
    if (i) bar_sync<NB_PRE, 128>();
    if (i == 2) bar_arrive<NB_T0, 192>();
    const uint32_t o0 = ob + OFF_SLOT(i ? i - 1 : 10);
    sts128(o0, make_uint4(__byte_perm(kv[7], kv[6], 0x5410), __byte_perm(kv[5], kv[4], 0x5410), __byte_perm(kv[3], kv[2], 0x5410), __byte_perm(kv[1], kv[0], 0x5410)));
    sts128((o0 + 128) ^ 16, make_uint4(__byte_perm(kv[7], kv[6], 0x7632), __byte_perm(kv[5], kv[4], 0x7632), __byte_perm(kv[3], kv[2], 0x7632), __byte_perm(kv[1], kv[0], 0x7632)));
    if ((i & 3) == 0) fence_async_smem();
    if (i == 0) bar_arrive<NB_PUB, 160>();
    sk += 256; ak -= 4096; ah += hstep; av += 4096;
  }
}

__global__ void __cluster_dims__(2, 1, 1) __launch_bounds__(NTHREADS, 1)
fused_kernel(const __grid_constant__ CUtensorMap mX, const __grid_constant__ CUtensorMap mHr, const __grid_constant__ CUtensorMap mHi,
             const __grid_constant__ CUtensorMap mCr, const __grid_constant__ CUtensorMap mCi,
             const __grid_constant__ CUtensorMap mT, const __grid_constant__ CUtensorMap mKh,
             const __grid_constant__ CUtensorMap mK, const __grid_constant__ CUtensorMap mV,
             const __grid_constant__ CUtensorMap mOut, const __grid_constant__ Params p) {
  extern __shared__ __align__(1024) unsigned char smem_raw[];
  const uint32_t base = smem_u32(smem_raw);
  const uint32_t bars = base + OFF_BAR;
  const int tid = threadIdx.x;
  const int warp = __shfl_sync(0xffffffffu, tid >> 5, 0), lane = tid & 31;
  const int wgi = warp >> 2, w = warp & 3, wt = tid & 127;
  const int cta = blockIdx.x, cid = blockIdx.x >> 1;
  const uint32_t rank = cta & 1;
  int gp, gr;
  {
    const int t = cid - 4, q7 = ((t - 32) * 37) >> 8;
    if (t < 0) { gp = 0; gr = 4 + cid; }
    else if (t < 32) { gp = t & 7; gr = t >> 3; }
    else { gp = t - 31 - 7 * q7; gr = 4 + q7; }
  }
  const int tb = 2 * gp + (gr >> 2), db = gr & 3;
  const int odd = db & 1;
  const int ch0 = (cta >> 5) * 160 + (cta & 31);

  if (warp < 15 && elect_one()) {
#pragma unroll 1
    for (int b = XOWN + 2 * warp; b < min(XOWN + 2 + 2 * warp, 31); b++) {
      mbar_init(bars + 8 * b, (b >= 5 && b < 10) ? 4 : (b >= 22 && b < 28 ? 2 : 1));
      uint32_t by = 8192 + 960 + 1280;
      if (b >= 11) by = 8192;
      if (b >= 15) by = 10240;
      if (b >= 17) by = 4096;
      if (b >= 10 && b < 22) mbar_expect_tx(bars + 8 * b, by);
    }
    asm volatile("fence.mbarrier_init.release.cluster;" ::: "memory");
  }
  __syncwarp();
  if (wgi == 3) {
    reg_dec<R_AUX>();
    if (warp == 15) {
      const CUtensorMap* mC = rank ? &mCi : &mCr;
      const bool leader = elect_one();
      if (leader) { STAMP(0); STAMPC(30); VAL(55, smid()); VAL(56, tb * 4 + db); prefetch_map(mC); prefetch_map(&mX); }
      int s = 0, ph = 1;
#pragma unroll 1
      for (int it = 0; it < 32; it++) {
        const uint32_t sa = base + s * STAGE_BYTES, bf = BAR_FULL(s);
        if (it >= STAGES) mbar_wait(BAR_EMPTY(s), ph);
        if (leader) {
          if (it < XOWN) {
            mbar_init(bf, 1);
            asm volatile("fence.mbarrier_init.release.cluster;" ::: "memory");
          }
          mbar_expect_tx(bf, STAGE_BYTES);
          tma_load_2d(sa, mC, it * 64, tb * 128, bf);
          tma_load_3d_mc(sa + A_BYTES + rank * 10240, &mX, 0, it * 64 + rank * 32, db * 5, bf, it < XOWN ? 1 + rank : 3);
          if (it < XOWN) tma_load_3d(sa + A_BYTES + (rank ^ 1) * 10240, &mX, 0, it * 64 + (rank ^ 1) * 32, db * 5, bf);
        }
        __syncwarp();
        if (it == XOWN - 1) { cluster_arrive(); cluster_wait(); }
        if (leader) {
          const unsigned e = it - G_KV;
          if (e < 10) tma_load_3d(base + OFF_SLOT((e & 1) ? e >> 1 : 9 - (e >> 1)), (e & 1) ? &mV : &mK, 0, (cta >> 2) * 64, (cta & 3) * 5 + (e >> 1), BAR_KV(e >> 1));
          if (e == 0) {
            tma_load_3d(base + OFF_HALO, &mKh, 0, (cta >> 2) * 64 - 3, (cta & 3) * 5, BAR_KV(0));
            bulk_load(base + OFF_SK, p.shift_k + (cta & 3) * 640, 1280, BAR_KV(0));
          }
          if ((unsigned)(it - G_T) < 4) bulk_prefetch(p.ssm_k + (size_t)(ch0 + 32 * (it - G_T + 1)) * 2048, 4096);
          if ((unsigned)(it - G_Q) < 2) bulk_prefetch(p.q + (size_t)(cta * 2 + it - G_Q) * 8 * 640, 8 * 1280);
          if (it == G_H) bulk_prefetch((rank ? p.hi : p.hr) + (size_t)cid * 10 * 640, 10 * 1280);
        }
        if (++s == STAGES) { s = 0; ph ^= 1; }
      }
      if (leader) {
        const CUtensorMap* mH = rank ? &mHi : &mHr;
        const int kb5 = (db >> 1) * 5;
        unsigned char* ub = g_u + (size_t)(tb * 2 + rank) * 10 * A_BYTES;
        unsigned* flags = g_flag + (tb * 2 + rank) * 32;
        unsigned tag = 0, seen = 0;
#pragma unroll 1
        for (int i = 7 - NBE; i < 15; i++) {
          const int j = i < 7 ? i - (7 - NBE) : i - 5;
          const int kb = (j < 5) ? kb5 + (odd ? (j < 2 ? j + 3 : (j == 2 ? 2 : j - 3)) : j) : j - kb5;
          s = (32 + j) % STAGES;
          const uint32_t sa = base + s * STAGE_BYTES, bf = BAR_FULL(s);
          if (i >= 7) {
            const unsigned need = 1u << (j < 5 ? db ^ 1 : ((db ^ 2) & 2) + (j >= 7));
            if (!(seen & need)) {
#pragma unroll 1
              for (int tries = 0; tries < (1 << 18); tries++) {
                uint4 f;
                asm volatile("ld.acquire.gpu.global.v4.u32 {%0,%1,%2,%3}, [%4];" : "=r"(f.x), "=r"(f.y), "=r"(f.z), "=r"(f.w) : "l"(flags) : "memory");
                seen = (f.x == tag) | (f.y == tag) << 1 | (f.z == tag) << 2 | (f.w == tag) << 3;
                if (seen & need) break;
              }
              fence_async_all();
            }
            if (i == 7) STAMP(4);
            if (i == 12) STAMP(5);
          }
          if (i < 7 || j >= NBE) {
            mbar_wait(BAR_EMPTY(s), ((32 + j) / STAGES & 1) ^ 1);
            mbar_expect_tx(bf, B_BYTES + (j < 2 ? 0 : (j == 2 ? 8192 : A_BYTES)));
            tma_load_2d(sa + A_BYTES, mH, kb * 64, db * 160 + rank * 80, bf);
            tma_load_2d(sa + A_BYTES + 10240, mH, kb * 64, db * 160 + (rank ^ 1) * 80, bf);
          }
          if (i >= 7) {
            const uint32_t off = i == 7 ? (odd ^ 1) * 4096 : 0, sz = i == 7 ? 4096 : 8192;
            bulk_load(sa + off, ub + kb * A_BYTES + off, sz, bf);
            bulk_load(sa + off + 8192, ub + kb * A_BYTES + off + 8192, sz, bf);
          }
          if (i == 9 - NBE) {
            const uint32_t s0 = base + (32 % STAGES) * STAGE_BYTES;
            unsigned char* d0 = ub + (kb5 + (odd ? 3 : 0)) * A_BYTES;
            mbar_wait(BAR_EPOCH, 0);
            tag = lds32(EPOCH_WORD) + 1;
#pragma unroll 1
            for (int g = 8192; g >= 0; g -= 8192) {
              mbar_wait(BAR_EPI(g >> 13), 0);
              bulk_store(ub + kb * A_BYTES + odd * 4096 + g, sa + odd * 4096 + g, 4096);
              bulk_store(d0 + g, s0 + g, 8192);
              bulk_store(d0 + A_BYTES + g, s0 + STAGE_BYTES + g, 8192);
            }
            bulk_commit();
            STAMP(23);
          }
          if (i == 6) {
            bulk_wait_all();
            st_relaxed(&flags[db], tag);
            STAMP(3);
          }
          if (i == G_F) mbar_arrive(BAR_EPOCH);
        }
      }
      __syncwarp();
    } else {
      cluster_arrive();
      cluster_wait();
      unsigned target = 0;
      const bool leader = elect_one();
      if (w == 1 && leader) {
        target = atomicAdd(&g_ticket, 1u) / NCTA;
        asm volatile("st.shared.u32 [%0], %1;" ::"r"(EPOCH_WORD), "r"(target) : "memory");
        mbar_arrive(BAR_EPOCH);
        target = (target + 1) * 32;
      }
      const uint32_t part = base + OFF_PART;
      const int tu = lane + w * 16;
      const __nv_bfloat16* hsrc = p.ssm_k + (size_t)ch0 * 2048 + tu * 8;
      mbar_wait_slow(BAR_KV(0), 0);
#pragma unroll 1
      for (int hs = -2; hs < 5; hs++) {
        const bool tab = hs < 3 && w != 1;
        uint4 hv[4];
        uint32_t hpv[4];
        hpv[0] = 0;
        if (tab) {
#pragma unroll
          for (int i = 0; i < 4; i++) {
            hv[i] = ldg128(hsrc + i * 512);
            if (i || wt) hpv[i] = ldg32(hsrc + i * 512 - 2);
          }
        }
        hsrc += 32 * 2048;
        const uint32_t dd = (uint32_t)__bfloat16_as_ushort(p.ssm_D[ch0 + 32 * max(hs, 0)]) * 0x10001u;
        asm volatile("bar.sync %0, %1;" ::"r"(hs > -2 ? NB_PFULL : (w == 1 ? NB_PUB : NB_T0)), "r"(hs > -2 ? 224 : (w == 1 ? 160 : 192)) : "memory");
        if (hs >= 0) {
#pragma unroll 1
          for (int mch = wt; mch < 256; mch += 96) {
            const int t0 = mch * 8;
            const int s0 = t0 ^ (((t0 >> 5) & 3) << 3) ^ (((t0 >> 5) & 1) << 2);
            float4 lo = lds128f(part + s0 * 4), hi = lds128f(part + (s0 ^ 4) * 4);
            if (mch >= 8) {
              const float4 l2 = lds128f(part + 8192 + s0 * 4), h2 = lds128f(part + 8192 + (s0 ^ 4) * 4);
              lo.x += l2.x; lo.y += l2.y; lo.z += l2.z; lo.w += l2.w;
              hi.x += h2.x; hi.y += h2.y; hi.z += h2.z; hi.w += h2.w;
            }
            const int cidx = 255 - mch;
            const uint32_t ua = base + u_off(hs) + ((cidx ^ ((cidx >> 3) & 1)) << 4);
            const uint4 u = lds128(ua);
            uint4 z;
            z.x = badd2(pack_bf16(lo.x, lo.y), bmul2(__byte_perm(u.w, 0, 0x1032), dd));
            z.y = badd2(pack_bf16(lo.z, lo.w), bmul2(__byte_perm(u.z, 0, 0x1032), dd));
            z.z = badd2(pack_bf16(hi.x, hi.y), bmul2(__byte_perm(u.y, 0, 0x1032), dd));
            z.w = badd2(pack_bf16(hi.z, hi.w), bmul2(__byte_perm(u.x, 0, 0x1032), dd));
            sts128(ua, z);
          }
          fence_async_smem();
        } else if (w == 1) {
          if (leader) {
            STAMP(hs == -2 ? 33 : 47);
#pragma unroll 1
            for (int i = hs + 2; i < 4 * hs + 9; i++) tma_store_2d(&mT, (31 - (cta >> 2)) * 64, (cta & 3) * 160 + 32 * i, base + OFF_SLOT(i ? i - 1 : 10));
            bulk_commit();
            bulk_wait_all();
            red_relaxed_add(&g_cnt[(4 * hs + 8 + (cta & 3)) * 32], 1u);
            STAMP(hs == -2 ? 34 : 48);
          }
          __syncwarp();
        }
        if (hs > -2 && hs < 4) bar_arrive<NB_PFREE, 224>();
        if (tab) {
          const uint32_t a = base + OFF_HT + ((hs & 1) ^ 1) * HT_BYTES + 32 + tu * 16;
          if (wt < 4) sts128(a - 32 + (wt >> 1) * (HC_BYTES - 32), make_uint4(0, 0, 0, 0));
#pragma unroll
          for (int i = 0; i < 4; i++) {
            sts128(a + i * 1024, hv[i]);
            sts128(a + i * 1024 + HC_BYTES, make_uint4(__byte_perm(hpv[i], hv[i].x, 0x5432), __byte_perm(hv[i].x, hv[i].y, 0x5432),
                                                       __byte_perm(hv[i].y, hv[i].z, 0x5432), __byte_perm(hv[i].z, hv[i].w, 0x5432)));
          }
          __syncwarp();
          if (leader) mbar_arrive(BAR_TAB(hs + 2));
        }
        if (hs >= 0) bar_sync<NB_AUX, 96>();
        if (w == 1) {
          if (hs < 0) {
            asm volatile("st.shared.v2.u32 [%0], {%1, %1};" ::"r"(base + u_off(hs + 2) + 4096 + lane * 8), "r"(0) : "memory");
            asm volatile("st.shared.v2.u32 [%0], {%1, %1};" ::"r"(base + u_off(2 * hs + 4) + 4096 + lane * 8), "r"(0) : "memory");
            fence_async_smem();
            __syncwarp();
          }
          if (leader) {
            if (hs < 0) {
              wait_ge(&g_cnt[(4 * hs + 8 + (cta >> 5)) * 32], target);
              STAMP(hs == -2 ? 35 : 49);
            }
            if (hs >= 0) {
              if (hs == 4) STAMP(20);
              bulk_store(g_z + (size_t)(ch0 + 32 * hs) * 2048, base + u_off(hs), 4096);
              bulk_commit();
              bulk_wait_all();
              if (hs >= 3) red_relaxed_add(&g_cnt[(4 * hs - 4 + (cta >> 5)) * 32], 1u);
              if (hs == 4) STAMP(42);
            }
            if (hs < 2) {
              fence_async_all();
#pragma unroll 1
              for (int c = hs < 0 ? hs + 2 : hs + 3; c <= (hs == -2 ? 0 : hs + 3); c++)
                bulk_load(base + u_off(c), g_t + (size_t)(ch0 + 32 * c) * 4096, 4096, BAR_U(c));
            }
          }
          __syncwarp();
        }
      }
      __syncwarp();
    }
  } else if (wgi == 0) {
    cluster_arrive();
    cluster_wait();
    reg_inc<R_CONV>();
    pre_phase(base, bars, wt, cta);
    if (wt == 0) STAMP(45);
    bar_arrive<NB_PFULL, 224>();
    const int g = lane >> 2, tig = lane & 3, ph = w & 1, lg = w >> 1;
    const int x00 = 64 * lg + 8 * ph + g + 2 * tig + 1;
    const uint32_t hp = base + OFF_HT + ((x00 & 1) ? HC_BYTES + 2 * (x00 + 1) : 2 * x00);
    const bool late = lg && tig < 2;
    uint32_t pw[2];
#pragma unroll
    for (int j = 0; j < 2; j++) {
      const int t = 16 * (127 + 4 * lg) - 32 * tig - 16 * j + 8 * ph + g;
      const int sw = t ^ (((t >> 5) & 3) << 3) ^ (((t >> 5) & 1) << 2);
      pw[j] = base + OFF_PART + lg * 8192 + sw * 4;
    }
#pragma unroll 1
    for (int c = 0; c < 5; c++) {
      mbar_wait_slow(BAR_TAB(c), 0);
      mbar_wait_slow(BAR_U(c), 0);
      if (wt == 0) STAMP(10 + 2 * c);
      conv_channel(hp + ((c & 1) ^ 1) * HT_BYTES, (uint32_t)mkdesc(base + u_off(c), 16, 256, 3), pw, late);
      if (wt == 0) STAMP(11 + 2 * c);
      bar_arrive<NB_PFULL, 224>();
    }
  } else {
    cluster_arrive();
    cluster_wait();
    reg_dec<R_GEMM>();
    const int wg = wgi - 1;
    float acc[80];
    int s = 0, ph = 0;
#pragma unroll 1
    for (int it = 0; it < 32; it++) {
      mbar_wait(BAR_FULL(s), ph);
      const uint32_t sa = base + s * STAGE_BYTES + wg * 8192, sb = base + s * STAGE_BYTES + A_BYTES;
      const uint64_t da = mkdesc(sa, 16, 1024, 1), db_ = mkdesc(sb, 2048, 512, 2);
#pragma unroll
      for (int i = 0; i < 80; i++) asm volatile("" : "+f"(acc[i])::"memory");
      wg_fence();
      wgmma_ss_tb160(acc, da, db_, it != 0);
      wgmma_ss_tb160(acc, da + 2, db_ + 64, 1);
      wgmma_ss_tb160(acc, da + 4, db_ + 640, 1);
      wgmma_ss_tb160(acc, da + 6, db_ + 704, 1);
      wg_commit();
      wg_wait<0>();
      if (wt < 2) mbar_arrive_cta(BAR_EMPTY(s), wt);
      if (++s == STAGES) { s = 0; ph ^= 1; }
    }
#pragma unroll
    for (int i = 0; i < 80; i++) asm volatile("" : "+f"(acc[i])::"memory");
    if (wt == 0) STAMP(wg ? 38 : 2);
    const int m = lane >> 3, i8 = lane & 7;
    {
      const int row = 16 * w + 8 * (m & 1) + i8;
      const uint32_t ad0 = base + (32 % STAGES) * STAGE_BYTES + wg * 8192 + row * 64 + (((m >> 1) ^ ((row >> 1) & 3)) << 4);
#pragma unroll
      for (int lc = 0; lc < 5; lc++) {
        const int e0 = lc, e1 = lc == 0 ? 5 : lc - 1;
        const uint32_t ad = ad0 + (odd ? (e1 >> 1) * STAGE_BYTES + (e1 & 1) * 4096 : (e0 >> 1) * STAGE_BYTES + (e0 & 1) * 4096);
#pragma unroll
        for (int h = 0; h < 2; h++) {
          const int G = lc * 4 + h * 2;
          stmatrix_x4(ad ^ (h * 32), pack_bf16(acc[4 * G], acc[4 * G + 1]), pack_bf16(acc[4 * G + 2], acc[4 * G + 3]),
                      pack_bf16(acc[4 * G + 4], acc[4 * G + 5]), pack_bf16(acc[4 * G + 6], acc[4 * G + 7]));
        }
      }
      fence_async_smem();
      asm volatile("bar.sync %0, 128;" ::"r"(NB_G0 + wg) : "memory");
      if (wt == 0) { mbar_arrive(BAR_EPI(wg)); STAMP(36 + wg); }
    }
#pragma unroll 1
    for (int it = 32; it < 42; it++) {
      mbar_wait(BAR_FULL(s), ph);
      const uint32_t sa = base + s * STAGE_BYTES + wg * 8192, sb = base + s * STAGE_BYTES + A_BYTES;
      const uint64_t da = mkdesc(sa, 16, 512, 2), db_ = mkdesc(sb, 16, 1024, 1);
#pragma unroll
      for (int i = 0; i < 80; i++) asm volatile("" : "+f"(acc[i])::"memory");
      wg_fence();
      wgmma_ss<160>(acc, da, db_, it != 32);
      wgmma_ss<160>(acc, da + 2, db_ + 2, 1);
      wgmma_ss<160>(acc, da + 256, db_ + 4, 1);
      wgmma_ss<160>(acc, da + 258, db_ + 6, 1);
      wg_commit();
      wg_wait<0>();
      if (wt < 2) mbar_arrive(BAR_EMPTY(s));
      if (it == 42 - STAGES && wt == 0) mbar_arrive_cta(BAR_XFREE, rank ^ 1);
      if (++s == STAGES) { s = 0; ph ^= 1; }
    }
#pragma unroll
    for (int i = 0; i < 80; i++) asm volatile("" : "+f"(acc[i])::"memory");
    if (wt == 0) STAMP(wg ? 41 : 6);
    {
      const uint32_t xw = base + ((42 - STAGES) % STAGES) * STAGE_BYTES + wg * 10240 + w * 2560, xb = xw + lane * 16;
      const uint32_t rxb = mapa(xb, rank ^ 1), rbar = mapa(BAR_XFULL(wg), rank ^ 1);
      mbar_wait(BAR_XFREE, 0);
#pragma unroll
      for (int i = 0; i < 5; i++)
        st_async128(rxb + i * 512, make_uint4(pack_bf16(acc[40 + 8 * i], acc[40 + 8 * i + 1]), pack_bf16(acc[40 + 8 * i + 2], acc[40 + 8 * i + 3]),
                                              pack_bf16(acc[40 + 8 * i + 4], acc[40 + 8 * i + 5]), pack_bf16(acc[40 + 8 * i + 6], acc[40 + 8 * i + 7])), rbar);
      if (wg == 0 && wt == 0) STAMP(40);
      const float sk = rank ? -1.f : 1.f;
      const uint32_t sr = rank ? 0u : 0x80000000u;
      mbar_wait(BAR_XFULL(wg), 0);
      if (wg == 0 && wt == 0) STAMP(28);
      uint4 r[5];
#pragma unroll
      for (int i = 0; i < 5; i++) r[i] = lds128(xb + i * 512);
      __syncwarp();
      const uint32_t ad = xw + (8 * (m & 1) + i8) * 160 + (m >> 1) * 16;
      auto comb = [&](int i, uint32_t v) {
        return pack_bf16(fmaf(acc[i], sk, __uint_as_float((v << 16) + sr)), fmaf(acc[i + 1], sk, __uint_as_float((v & 0xffff0000u) ^ sr)));
      };
#pragma unroll
      for (int i = 0; i < 5; i++) stmatrix_x4(ad + i * 32, comb(8 * i, r[i].x), comb(8 * i + 2, r[i].y), comb(8 * i + 4, r[i].z), comb(8 * i + 6, r[i].w));
      fence_async_smem();
      __syncwarp();
      if (elect_one()) {
        tma_store_2d(&mOut, db * 160 + rank * 80, tb * 128 + wg * 64 + w * 16, xw);
        bulk_commit();
        bulk_wait_read();
      }
      __syncwarp();
      if (wg == 0 && wt == 0) { STAMP(7); STAMPC(31); }
    }
  }
  if (warp < 4 || warp == 14) fin_phase(p, bars, min(warp, 4), lane, cta);
  KERNEL_END();
}

typedef CUresult (*PFN_encodeTiled)(CUtensorMap*, CUtensorMapDataType, cuuint32_t, void*, const cuuint64_t*, const cuuint64_t*,
                                    const cuuint32_t*, const cuuint32_t*, CUtensorMapInterleave, CUtensorMapSwizzle,
                                    CUtensorMapL2promotion, CUtensorMapFloatOOBfill);

static CUtensorMap make_map(PFN_encodeTiled enc, const void* ptr, uint64_t inner, uint64_t outer, uint32_t box_inner, uint32_t box_outer,
                            CUtensorMapSwizzle swz, CUtensorMapL2promotion prom = CU_TENSOR_MAP_L2_PROMOTION_L2_128B) {
  CUtensorMap m;
  cuuint64_t dims[2] = {inner, outer};
  cuuint64_t strides[1] = {inner * 2};
  cuuint32_t box[2] = {box_inner, box_outer};
  cuuint32_t es[2] = {1, 1};
  enc(&m, CU_TENSOR_MAP_DATA_TYPE_BFLOAT16, 2, const_cast<void*>(ptr), dims, strides, box, es, CU_TENSOR_MAP_INTERLEAVE_NONE, swz,
      prom, CU_TENSOR_MAP_FLOAT_OOB_FILL_NONE);
  return m;
}

extern "C" void kernel_launch(void* const* d_in, const int* in_sizes, int n_in, void* d_out, int out_size) {
  static PFN_encodeTiled enc = nullptr;
  static void* gt = nullptr;
  if (!enc) {
    cudaGetSymbolAddress(&gt, g_t);
    void* fp = nullptr;
    cudaDriverEntryPointQueryResult qr;
    cudaGetDriverEntryPoint("cuTensorMapEncodeTiled", &fp, cudaEnableDefault, &qr);
    enc = (PFN_encodeTiled)fp;
    cudaFuncSetAttribute(fused_kernel, cudaFuncAttributeMaxDynamicSharedMemorySize, SMEM_BYTES);
  }
  auto map3 = [&](const void* ptr, uint32_t rows, uint32_t groups, CUtensorMapSwizzle swz) {
    CUtensorMap m;
    cuuint64_t dims[3] = {32, 2048, 20};
    cuuint64_t strides[2] = {1280, 64};
    cuuint32_t box[3] = {32, rows, groups};
    cuuint32_t es[3] = {1, 1, 1};
    enc(&m, CU_TENSOR_MAP_DATA_TYPE_BFLOAT16, 3, const_cast<void*>(ptr), dims, strides, box, es, CU_TENSOR_MAP_INTERLEAVE_NONE, swz,
        CU_TENSOR_MAP_L2_PROMOTION_L2_128B, CU_TENSOR_MAP_FLOAT_OOB_FILL_NONE);
    return m;
  };
  CUtensorMap mX = map3(d_in[0], 32, 5, CU_TENSOR_MAP_SWIZZLE_64B);
  CUtensorMap mKh = map3(d_in[6], 3, 5, CU_TENSOR_MAP_SWIZZLE_NONE);
  CUtensorMap mK = map3(d_in[6], 64, 1, CU_TENSOR_MAP_SWIZZLE_NONE);
  CUtensorMap mV = map3(d_in[7], 64, 1, CU_TENSOR_MAP_SWIZZLE_NONE);
  CUtensorMap mCr = make_map(enc, d_in[1], 2048, 2048, 64, 128, CU_TENSOR_MAP_SWIZZLE_128B);
  CUtensorMap mCi = make_map(enc, d_in[2], 2048, 2048, 64, 128, CU_TENSOR_MAP_SWIZZLE_128B);
  CUtensorMap mHr = make_map(enc, d_in[3], 640, 640, 64, 80, CU_TENSOR_MAP_SWIZZLE_128B);
  CUtensorMap mHi = make_map(enc, d_in[4], 640, 640, 64, 80, CU_TENSOR_MAP_SWIZZLE_128B);
  CUtensorMap mT = make_map(enc, gt, 2048, 640, 64, 32, CU_TENSOR_MAP_SWIZZLE_128B);
  CUtensorMap mOut = make_map(enc, d_out, 1280, 2048, 80, 16, CU_TENSOR_MAP_SWIZZLE_NONE);
  Params p;
  p.hr = (const __nv_bfloat16*)d_in[3];
  p.hi = (const __nv_bfloat16*)d_in[4];
  p.q = (const __nv_bfloat16*)d_in[5];
  p.shift_k = (const __nv_bfloat16*)d_in[8];
  p.ssm_k = (const __nv_bfloat16*)d_in[9];
  p.ssm_D = (const __nv_bfloat16*)d_in[10];
  p.out = (__nv_bfloat16*)d_out;
  fused_kernel<<<NCTA, NTHREADS, SMEM_BYTES>>>(mX, mHr, mHi, mCr, mCi, mT, mKh, mK, mV, mOut, p);
}
```

```cpp
#include <cuda_runtime.h>
#include <cuda.h>
#include <cuda_bf16.h>
#include <stdint.h>

#define STAGES 5
#define G_KV 5
#define G_F 13
#define XOWN 1
#define PIPE 0
#define PR_X 2
#define PR_K 2
#define PR_C 2
#define NBE 7
#define FLI 4
#define EARLYQ 1
#define HSH 1
#define WPUB 2
#define FPF 3
#define RFAST 1
#define CTRC 4
#define NSPL 0
#define PL 4
#define PSLP 100
#define CPRI 2
#define G_Q 29
#define G_H 26
#define G_T 14
#define DI 3
#define R_CONV 184
#define R_GEMM 120
#define R_AUX 88
#define NCTA 128
#define A_BYTES 16384
#define B_BYTES 20480
#define STAGE_BYTES 36864
#define NTHREADS 512

#define OFF_PART   (STAGES * STAGE_BYTES)
#define U_BYTES    4352
#define OFF_UB     (OFF_PART + 16384)
#define OFF_HT     (OFF_UB + 2 * U_BYTES)
#define HC_BYTES   4128
#define HT_BYTES   8256
#define OFF_UA     (OFF_PART + 41728)
#define OFF_BAR    (OFF_PART + 46080)
#define OFF_SK     (OFF_BAR + 256)
#define SMEM_BYTES (OFF_SK + 1280)
#define OFF_HALO   OFF_PART
#define OFF_SLOT(i) (OFF_PART + 1024 + (i) * 4096)
__device__ __forceinline__ uint32_t u_off(int c) { return (c == 0 || c == 3) ? OFF_UA : (c == 2 ? OFF_UB + U_BYTES : OFF_UB); }

__device__ __align__(1024) unsigned char g_u[16 * 2 * 10 * A_BYTES];
__device__ __align__(1024) unsigned char g_t[1280 * 4096];
__device__ __align__(128) unsigned g_flag[32 * 32];
__device__ __align__(128) unsigned g_cnt[16 * 32];
__device__ unsigned g_ticket;
#define STAMP(i) do {} while (0)
#define ITC(i) do {} while (0)
#define STAMPC(i) do {} while (0)
#define VAL(i, v) do {} while (0)

template<int N> __device__ __forceinline__ void wgmma_ss(float* d, uint64_t a, uint64_t b, int s);
template<int N> __device__ __forceinline__ void wgmma_rs(float* d, uint32_t a0, uint32_t a1, uint32_t a2, uint32_t a3, uint32_t b, int off, int s);
template<> __device__ __forceinline__ void wgmma_ss<160>(float* d, uint64_t descA, uint64_t descB, int scaleD) {
  asm volatile("{\n.reg .pred p;\nsetp.ne.b32 p, %82, 0;\n"
    "wgmma.mma_async.sync.aligned.m64n160k16.f32.bf16.bf16 {%0,%1,%2,%3,%4,%5,%6,%7,%8,%9,%10,%11,%12,%13,%14,%15,%16,%17,%18,%19,%20,%21,%22,%23,%24,%25,%26,%27,%28,%29,%30,%31,%32,%33,%34,%35,%36,%37,%38,%39,%40,%41,%42,%43,%44,%45,%46,%47,%48,%49,%50,%51,%52,%53,%54,%55,%56,%57,%58,%59,%60,%61,%62,%63,%64,%65,%66,%67,%68,%69,%70,%71,%72,%73,%74,%75,%76,%77,%78,%79}, %80, %81, p, 1, 1, 0, 0;\n}\n"
    : "+f"(d[0]),"+f"(d[1]),"+f"(d[2]),"+f"(d[3]),"+f"(d[4]),"+f"(d[5]),"+f"(d[6]),"+f"(d[7]),"+f"(d[8]),"+f"(d[9]),"+f"(d[10]),"+f"(d[11]),"+f"(d[12]),"+f"(d[13]),"+f"(d[14]),"+f"(d[15]),"+f"(d[16]),"+f"(d[17]),"+f"(d[18]),"+f"(d[19]),"+f"(d[20]),"+f"(d[21]),"+f"(d[22]),"+f"(d[23]),"+f"(d[24]),"+f"(d[25]),"+f"(d[26]),"+f"(d[27]),"+f"(d[28]),"+f"(d[29]),"+f"(d[30]),"+f"(d[31]),"+f"(d[32]),"+f"(d[33]),"+f"(d[34]),"+f"(d[35]),"+f"(d[36]),"+f"(d[37]),"+f"(d[38]),"+f"(d[39]),"+f"(d[40]),"+f"(d[41]),"+f"(d[42]),"+f"(d[43]),"+f"(d[44]),"+f"(d[45]),"+f"(d[46]),"+f"(d[47]),"+f"(d[48]),"+f"(d[49]),"+f"(d[50]),"+f"(d[51]),"+f"(d[52]),"+f"(d[53]),"+f"(d[54]),"+f"(d[55]),"+f"(d[56]),"+f"(d[57]),"+f"(d[58]),"+f"(d[59]),"+f"(d[60]),"+f"(d[61]),"+f"(d[62]),"+f"(d[63]),"+f"(d[64]),"+f"(d[65]),"+f"(d[66]),"+f"(d[67]),"+f"(d[68]),"+f"(d[69]),"+f"(d[70]),"+f"(d[71]),"+f"(d[72]),"+f"(d[73]),"+f"(d[74]),"+f"(d[75]),"+f"(d[76]),"+f"(d[77]),"+f"(d[78]),"+f"(d[79])
    : "l"(descA),"l"(descB),"r"(scaleD));
}
__device__ __forceinline__ void wgmma_ss_tb160(float* d, uint64_t descA, uint64_t descB, int scaleD) {
  asm volatile("{\n.reg .pred p;\nsetp.ne.b32 p, %82, 0;\n"
    "wgmma.mma_async.sync.aligned.m64n160k16.f32.bf16.bf16 {%0,%1,%2,%3,%4,%5,%6,%7,%8,%9,%10,%11,%12,%13,%14,%15,%16,%17,%18,%19,%20,%21,%22,%23,%24,%25,%26,%27,%28,%29,%30,%31,%32,%33,%34,%35,%36,%37,%38,%39,%40,%41,%42,%43,%44,%45,%46,%47,%48,%49,%50,%51,%52,%53,%54,%55,%56,%57,%58,%59,%60,%61,%62,%63,%64,%65,%66,%67,%68,%69,%70,%71,%72,%73,%74,%75,%76,%77,%78,%79}, %80, %81, p, 1, 1, 0, 1;\n}\n"
    : "+f"(d[0]),"+f"(d[1]),"+f"(d[2]),"+f"(d[3]),"+f"(d[4]),"+f"(d[5]),"+f"(d[6]),"+f"(d[7]),"+f"(d[8]),"+f"(d[9]),"+f"(d[10]),"+f"(d[11]),"+f"(d[12]),"+f"(d[13]),"+f"(d[14]),"+f"(d[15]),"+f"(d[16]),"+f"(d[17]),"+f"(d[18]),"+f"(d[19]),"+f"(d[20]),"+f"(d[21]),"+f"(d[22]),"+f"(d[23]),"+f"(d[24]),"+f"(d[25]),"+f"(d[26]),"+f"(d[27]),"+f"(d[28]),"+f"(d[29]),"+f"(d[30]),"+f"(d[31]),"+f"(d[32]),"+f"(d[33]),"+f"(d[34]),"+f"(d[35]),"+f"(d[36]),"+f"(d[37]),"+f"(d[38]),"+f"(d[39]),"+f"(d[40]),"+f"(d[41]),"+f"(d[42]),"+f"(d[43]),"+f"(d[44]),"+f"(d[45]),"+f"(d[46]),"+f"(d[47]),"+f"(d[48]),"+f"(d[49]),"+f"(d[50]),"+f"(d[51]),"+f"(d[52]),"+f"(d[53]),"+f"(d[54]),"+f"(d[55]),"+f"(d[56]),"+f"(d[57]),"+f"(d[58]),"+f"(d[59]),"+f"(d[60]),"+f"(d[61]),"+f"(d[62]),"+f"(d[63]),"+f"(d[64]),"+f"(d[65]),"+f"(d[66]),"+f"(d[67]),"+f"(d[68]),"+f"(d[69]),"+f"(d[70]),"+f"(d[71]),"+f"(d[72]),"+f"(d[73]),"+f"(d[74]),"+f"(d[75]),"+f"(d[76]),"+f"(d[77]),"+f"(d[78]),"+f"(d[79])
    : "l"(descA),"l"(descB),"r"(scaleD));
}
template<> __device__ __forceinline__ void wgmma_ss<80>(float* d, uint64_t descA, uint64_t descB, int scaleD) {
  asm volatile("{\n.reg .pred p;\nsetp.ne.b32 p, %42, 0;\n"
    "wgmma.mma_async.sync.aligned.m64n80k16.f32.bf16.bf16 {%0,%1,%2,%3,%4,%5,%6,%7,%8,%9,%10,%11,%12,%13,%14,%15,%16,%17,%18,%19,%20,%21,%22,%23,%24,%25,%26,%27,%28,%29,%30,%31,%32,%33,%34,%35,%36,%37,%38,%39}, %40, %41, p, 1, 1, 0, 0;\n}\n"
    : "+f"(d[0]),"+f"(d[1]),"+f"(d[2]),"+f"(d[3]),"+f"(d[4]),"+f"(d[5]),"+f"(d[6]),"+f"(d[7]),"+f"(d[8]),"+f"(d[9]),"+f"(d[10]),"+f"(d[11]),"+f"(d[12]),"+f"(d[13]),"+f"(d[14]),"+f"(d[15]),"+f"(d[16]),"+f"(d[17]),"+f"(d[18]),"+f"(d[19]),"+f"(d[20]),"+f"(d[21]),"+f"(d[22]),"+f"(d[23]),"+f"(d[24]),"+f"(d[25]),"+f"(d[26]),"+f"(d[27]),"+f"(d[28]),"+f"(d[29]),"+f"(d[30]),"+f"(d[31]),"+f"(d[32]),"+f"(d[33]),"+f"(d[34]),"+f"(d[35]),"+f"(d[36]),"+f"(d[37]),"+f"(d[38]),"+f"(d[39])
    : "l"(descA),"l"(descB),"r"(scaleD));
}
template<> __device__ __forceinline__ void wgmma_rs<16>(float* d, uint32_t a0, uint32_t a1, uint32_t a2, uint32_t a3, uint32_t descLo, int off, int scaleD) {
  asm volatile("{\n.reg .pred p;\n.reg .b32 t;\n.reg .b64 d;\nsetp.ne.b32 p, %14, 0;\nadd.u32 t, %12, %13;\nmov.b64 d, {t, 0xC0000010};\n"
    "wgmma.mma_async.sync.aligned.m64n16k16.f32.bf16.bf16 {%0,%1,%2,%3,%4,%5,%6,%7}, {%8,%9,%10,%11}, d, p, 1, 1, 0;\n}\n"
    : "+f"(d[0]),"+f"(d[1]),"+f"(d[2]),"+f"(d[3]),"+f"(d[4]),"+f"(d[5]),"+f"(d[6]),"+f"(d[7])
    : "r"(a0),"r"(a1),"r"(a2),"r"(a3),"r"(descLo),"r"(off),"r"(scaleD));
}
template<> __device__ __forceinline__ void wgmma_rs<32>(float* d, uint32_t a0, uint32_t a1, uint32_t a2, uint32_t a3, uint32_t descLo, int off, int scaleD) {
  asm volatile("{\n.reg .pred p;\n.reg .b32 t;\n.reg .b64 d;\nsetp.ne.b32 p, %22, 0;\nadd.u32 t, %20, %21;\nmov.b64 d, {t, 0xC0000010};\n"
    "wgmma.mma_async.sync.aligned.m64n32k16.f32.bf16.bf16 {%0,%1,%2,%3,%4,%5,%6,%7,%8,%9,%10,%11,%12,%13,%14,%15}, {%16,%17,%18,%19}, d, p, 1, 1, 0;\n}\n"
    : "+f"(d[0]),"+f"(d[1]),"+f"(d[2]),"+f"(d[3]),"+f"(d[4]),"+f"(d[5]),"+f"(d[6]),"+f"(d[7]),"+f"(d[8]),"+f"(d[9]),"+f"(d[10]),"+f"(d[11]),"+f"(d[12]),"+f"(d[13]),"+f"(d[14]),"+f"(d[15])
    : "r"(a0),"r"(a1),"r"(a2),"r"(a3),"r"(descLo),"r"(off),"r"(scaleD));
}
template<> __device__ __forceinline__ void wgmma_rs<48>(float* d, uint32_t a0, uint32_t a1, uint32_t a2, uint32_t a3, uint32_t descLo, int off, int scaleD) {
  asm volatile("{\n.reg .pred p;\n.reg .b32 t;\n.reg .b64 d;\nsetp.ne.b32 p, %30, 0;\nadd.u32 t, %28, %29;\nmov.b64 d, {t, 0xC0000010};\n"
    "wgmma.mma_async.sync.aligned.m64n48k16.f32.bf16.bf16 {%0,%1,%2,%3,%4,%5,%6,%7,%8,%9,%10,%11,%12,%13,%14,%15,%16,%17,%18,%19,%20,%21,%22,%23}, {%24,%25,%26,%27}, d, p, 1, 1, 0;\n}\n"
    : "+f"(d[0]),"+f"(d[1]),"+f"(d[2]),"+f"(d[3]),"+f"(d[4]),"+f"(d[5]),"+f"(d[6]),"+f"(d[7]),"+f"(d[8]),"+f"(d[9]),"+f"(d[10]),"+f"(d[11]),"+f"(d[12]),"+f"(d[13]),"+f"(d[14]),"+f"(d[15]),"+f"(d[16]),"+f"(d[17]),"+f"(d[18]),"+f"(d[19]),"+f"(d[20]),"+f"(d[21]),"+f"(d[22]),"+f"(d[23])
    : "r"(a0),"r"(a1),"r"(a2),"r"(a3),"r"(descLo),"r"(off),"r"(scaleD));
}
template<> __device__ __forceinline__ void wgmma_rs<64>(float* d, uint32_t a0, uint32_t a1, uint32_t a2, uint32_t a3, uint32_t descLo, int off, int scaleD) {
  asm volatile("{\n.reg .pred p;\n.reg .b32 t;\n.reg .b64 d;\nsetp.ne.b32 p, %38, 0;\nadd.u32 t, %36, %37;\nmov.b64 d, {t, 0xC0000010};\n"
    "wgmma.mma_async.sync.aligned.m64n64k16.f32.bf16.bf16 {%0,%1,%2,%3,%4,%5,%6,%7,%8,%9,%10,%11,%12,%13,%14,%15,%16,%17,%18,%19,%20,%21,%22,%23,%24,%25,%26,%27,%28,%29,%30,%31}, {%32,%33,%34,%35}, d, p, 1, 1, 0;\n}\n"
    : "+f"(d[0]),"+f"(d[1]),"+f"(d[2]),"+f"(d[3]),"+f"(d[4]),"+f"(d[5]),"+f"(d[6]),"+f"(d[7]),"+f"(d[8]),"+f"(d[9]),"+f"(d[10]),"+f"(d[11]),"+f"(d[12]),"+f"(d[13]),"+f"(d[14]),"+f"(d[15]),"+f"(d[16]),"+f"(d[17]),"+f"(d[18]),"+f"(d[19]),"+f"(d[20]),"+f"(d[21]),"+f"(d[22]),"+f"(d[23]),"+f"(d[24]),"+f"(d[25]),"+f"(d[26]),"+f"(d[27]),"+f"(d[28]),"+f"(d[29]),"+f"(d[30]),"+f"(d[31])
    : "r"(a0),"r"(a1),"r"(a2),"r"(a3),"r"(descLo),"r"(off),"r"(scaleD));
}
template<> __device__ __forceinline__ void wgmma_rs<80>(float* d, uint32_t a0, uint32_t a1, uint32_t a2, uint32_t a3, uint32_t descLo, int off, int scaleD) {
  asm volatile("{\n.reg .pred p;\n.reg .b32 t;\n.reg .b64 d;\nsetp.ne.b32 p, %46, 0;\nadd.u32 t, %44, %45;\nmov.b64 d, {t, 0xC0000010};\n"
    "wgmma.mma_async.sync.aligned.m64n80k16.f32.bf16.bf16 {%0,%1,%2,%3,%4,%5,%6,%7,%8,%9,%10,%11,%12,%13,%14,%15,%16,%17,%18,%19,%20,%21,%22,%23,%24,%25,%26,%27,%28,%29,%30,%31,%32,%33,%34,%35,%36,%37,%38,%39}, {%40,%41,%42,%43}, d, p, 1, 1, 0;\n}\n"
    : "+f"(d[0]),"+f"(d[1]),"+f"(d[2]),"+f"(d[3]),"+f"(d[4]),"+f"(d[5]),"+f"(d[6]),"+f"(d[7]),"+f"(d[8]),"+f"(d[9]),"+f"(d[10]),"+f"(d[11]),"+f"(d[12]),"+f"(d[13]),"+f"(d[14]),"+f"(d[15]),"+f"(d[16]),"+f"(d[17]),"+f"(d[18]),"+f"(d[19]),"+f"(d[20]),"+f"(d[21]),"+f"(d[22]),"+f"(d[23]),"+f"(d[24]),"+f"(d[25]),"+f"(d[26]),"+f"(d[27]),"+f"(d[28]),"+f"(d[29]),"+f"(d[30]),"+f"(d[31]),"+f"(d[32]),"+f"(d[33]),"+f"(d[34]),"+f"(d[35]),"+f"(d[36]),"+f"(d[37]),"+f"(d[38]),"+f"(d[39])
    : "r"(a0),"r"(a1),"r"(a2),"r"(a3),"r"(descLo),"r"(off),"r"(scaleD));
}
template<> __device__ __forceinline__ void wgmma_rs<96>(float* d, uint32_t a0, uint32_t a1, uint32_t a2, uint32_t a3, uint32_t descLo, int off, int scaleD) {
  asm volatile("{\n.reg .pred p;\n.reg .b32 t;\n.reg .b64 d;\nsetp.ne.b32 p, %54, 0;\nadd.u32 t, %52, %53;\nmov.b64 d, {t, 0xC0000010};\n"
    "wgmma.mma_async.sync.aligned.m64n96k16.f32.bf16.bf16 {%0,%1,%2,%3,%4,%5,%6,%7,%8,%9,%10,%11,%12,%13,%14,%15,%16,%17,%18,%19,%20,%21,%22,%23,%24,%25,%26,%27,%28,%29,%30,%31,%32,%33,%34,%35,%36,%37,%38,%39,%40,%41,%42,%43,%44,%45,%46,%47}, {%48,%49,%50,%51}, d, p, 1, 1, 0;\n}\n"
    : "+f"(d[0]),"+f"(d[1]),"+f"(d[2]),"+f"(d[3]),"+f"(d[4]),"+f"(d[5]),"+f"(d[6]),"+f"(d[7]),"+f"(d[8]),"+f"(d[9]),"+f"(d[10]),"+f"(d[11]),"+f"(d[12]),"+f"(d[13]),"+f"(d[14]),"+f"(d[15]),"+f"(d[16]),"+f"(d[17]),"+f"(d[18]),"+f"(d[19]),"+f"(d[20]),"+f"(d[21]),"+f"(d[22]),"+f"(d[23]),"+f"(d[24]),"+f"(d[25]),"+f"(d[26]),"+f"(d[27]),"+f"(d[28]),"+f"(d[29]),"+f"(d[30]),"+f"(d[31]),"+f"(d[32]),"+f"(d[33]),"+f"(d[34]),"+f"(d[35]),"+f"(d[36]),"+f"(d[37]),"+f"(d[38]),"+f"(d[39]),"+f"(d[40]),"+f"(d[41]),"+f"(d[42]),"+f"(d[43]),"+f"(d[44]),"+f"(d[45]),"+f"(d[46]),"+f"(d[47])
    : "r"(a0),"r"(a1),"r"(a2),"r"(a3),"r"(descLo),"r"(off),"r"(scaleD));
}
template<> __device__ __forceinline__ void wgmma_rs<112>(float* d, uint32_t a0, uint32_t a1, uint32_t a2, uint32_t a3, uint32_t descLo, int off, int scaleD) {
  asm volatile("{\n.reg .pred p;\n.reg .b32 t;\n.reg .b64 d;\nsetp.ne.b32 p, %62, 0;\nadd.u32 t, %60, %61;\nmov.b64 d, {t, 0xC0000010};\n"
    "wgmma.mma_async.sync.aligned.m64n112k16.f32.bf16.bf16 {%0,%1,%2,%3,%4,%5,%6,%7,%8,%9,%10,%11,%12,%13,%14,%15,%16,%17,%18,%19,%20,%21,%22,%23,%24,%25,%26,%27,%28,%29,%30,%31,%32,%33,%34,%35,%36,%37,%38,%39,%40,%41,%42,%43,%44,%45,%46,%47,%48,%49,%50,%51,%52,%53,%54,%55}, {%56,%57,%58,%59}, d, p, 1, 1, 0;\n}\n"
    : "+f"(d[0]),"+f"(d[1]),"+f"(d[2]),"+f"(d[3]),"+f"(d[4]),"+f"(d[5]),"+f"(d[6]),"+f"(d[7]),"+f"(d[8]),"+f"(d[9]),"+f"(d[10]),"+f"(d[11]),"+f"(d[12]),"+f"(d[13]),"+f"(d[14]),"+f"(d[15]),"+f"(d[16]),"+f"(d[17]),"+f"(d[18]),"+f"(d[19]),"+f"(d[20]),"+f"(d[21]),"+f"(d[22]),"+f"(d[23]),"+f"(d[24]),"+f"(d[25]),"+f"(d[26]),"+f"(d[27]),"+f"(d[28]),"+f"(d[29]),"+f"(d[30]),"+f"(d[31]),"+f"(d[32]),"+f"(d[33]),"+f"(d[34]),"+f"(d[35]),"+f"(d[36]),"+f"(d[37]),"+f"(d[38]),"+f"(d[39]),"+f"(d[40]),"+f"(d[41]),"+f"(d[42]),"+f"(d[43]),"+f"(d[44]),"+f"(d[45]),"+f"(d[46]),"+f"(d[47]),"+f"(d[48]),"+f"(d[49]),"+f"(d[50]),"+f"(d[51]),"+f"(d[52]),"+f"(d[53]),"+f"(d[54]),"+f"(d[55])
    : "r"(a0),"r"(a1),"r"(a2),"r"(a3),"r"(descLo),"r"(off),"r"(scaleD));
}
template<> __device__ __forceinline__ void wgmma_rs<128>(float* d, uint32_t a0, uint32_t a1, uint32_t a2, uint32_t a3, uint32_t descLo, int off, int scaleD) {
  asm volatile("{\n.reg .pred p;\n.reg .b32 t;\n.reg .b64 d;\nsetp.ne.b32 p, %70, 0;\nadd.u32 t, %68, %69;\nmov.b64 d, {t, 0xC0000010};\n"
    "wgmma.mma_async.sync.aligned.m64n128k16.f32.bf16.bf16 {%0,%1,%2,%3,%4,%5,%6,%7,%8,%9,%10,%11,%12,%13,%14,%15,%16,%17,%18,%19,%20,%21,%22,%23,%24,%25,%26,%27,%28,%29,%30,%31,%32,%33,%34,%35,%36,%37,%38,%39,%40,%41,%42,%43,%44,%45,%46,%47,%48,%49,%50,%51,%52,%53,%54,%55,%56,%57,%58,%59,%60,%61,%62,%63}, {%64,%65,%66,%67}, d, p, 1, 1, 0;\n}\n"
    : "+f"(d[0]),"+f"(d[1]),"+f"(d[2]),"+f"(d[3]),"+f"(d[4]),"+f"(d[5]),"+f"(d[6]),"+f"(d[7]),"+f"(d[8]),"+f"(d[9]),"+f"(d[10]),"+f"(d[11]),"+f"(d[12]),"+f"(d[13]),"+f"(d[14]),"+f"(d[15]),"+f"(d[16]),"+f"(d[17]),"+f"(d[18]),"+f"(d[19]),"+f"(d[20]),"+f"(d[21]),"+f"(d[22]),"+f"(d[23]),"+f"(d[24]),"+f"(d[25]),"+f"(d[26]),"+f"(d[27]),"+f"(d[28]),"+f"(d[29]),"+f"(d[30]),"+f"(d[31]),"+f"(d[32]),"+f"(d[33]),"+f"(d[34]),"+f"(d[35]),"+f"(d[36]),"+f"(d[37]),"+f"(d[38]),"+f"(d[39]),"+f"(d[40]),"+f"(d[41]),"+f"(d[42]),"+f"(d[43]),"+f"(d[44]),"+f"(d[45]),"+f"(d[46]),"+f"(d[47]),"+f"(d[48]),"+f"(d[49]),"+f"(d[50]),"+f"(d[51]),"+f"(d[52]),"+f"(d[53]),"+f"(d[54]),"+f"(d[55]),"+f"(d[56]),"+f"(d[57]),"+f"(d[58]),"+f"(d[59]),"+f"(d[60]),"+f"(d[61]),"+f"(d[62]),"+f"(d[63])
    : "r"(a0),"r"(a1),"r"(a2),"r"(a3),"r"(descLo),"r"(off),"r"(scaleD));
}

__device__ __forceinline__ uint32_t smem_u32(const void* p) { return (uint32_t)__cvta_generic_to_shared(p); }
__device__ __forceinline__ uint64_t mkdesc(uint32_t addr, uint32_t lbo, uint32_t sbo, int swz) {
  return (uint64_t)((addr & 0x3FFFF) >> 4) | ((uint64_t)(lbo >> 4) << 16) | ((uint64_t)(sbo >> 4) << 32) | ((uint64_t)swz << 62);
}
__device__ __forceinline__ unsigned long long gtime() { unsigned long long t; asm volatile("mov.u64 %0, %%globaltimer;" : "=l"(t)); return t; }
__device__ __forceinline__ void mbar_init(uint32_t bar, int count) { asm volatile("mbarrier.init.shared::cta.b64 [%0], %1;" ::"r"(bar), "r"(count) : "memory"); }
__device__ __forceinline__ void mbar_expect_tx(uint32_t bar, uint32_t bytes) { asm volatile("mbarrier.arrive.expect_tx.shared::cta.b64 _, [%0], %1;" ::"r"(bar), "r"(bytes) : "memory"); }
__device__ __forceinline__ void mbar_arrive(uint32_t bar) { asm volatile("mbarrier.arrive.shared::cta.b64 _, [%0];" ::"r"(bar) : "memory"); }
__device__ __forceinline__ void mbar_arrive_cta(uint32_t bar, uint32_t cta) {
  asm volatile("{\n.reg .b32 ra;\nmapa.shared::cluster.u32 ra, %0, %1;\nmbarrier.arrive.shared::cluster.b64 _, [ra];\n}\n" ::"r"(bar), "r"(cta) : "memory");
}
__device__ __forceinline__ void mbar_wait(uint32_t bar, uint32_t parity) {
  uint32_t ok;
  int tries = 0;
#pragma unroll 1
  do {
    asm volatile("{\n.reg .pred p;\nmbarrier.try_wait.parity.shared::cta.b64 p, [%1], %2;\nselp.u32 %0, 1, 0, p;\n}\n" : "=r"(ok) : "r"(bar), "r"(parity) : "memory");
  } while (!ok && ++tries < (1 << 17));
}
#define SLP 100
__device__ __forceinline__ void mbar_wait_slow(uint32_t bar, uint32_t parity) {
  uint32_t ok;
  int tries = 0;
#pragma unroll 1
  do {
    asm volatile("{\n.reg .pred p;\nmbarrier.test_wait.parity.shared::cta.b64 p, [%1], %2;\nselp.u32 %0, 1, 0, p;\n}\n" : "=r"(ok) : "r"(bar), "r"(parity) : "memory");
    if (!ok) __nanosleep(SLP);
  } while (!ok && ++tries < (1 << 17));
}
__device__ __forceinline__ uint32_t mbar_test(uint32_t bar, uint32_t parity) {
  uint32_t ok;
  asm volatile("{\n.reg .pred p;\nmbarrier.test_wait.parity.shared::cta.b64 p, [%1], %2;\nselp.u32 %0, 1, 0, p;\n}\n" : "=r"(ok) : "r"(bar), "r"(parity) : "memory");
  return ok;
}
__device__ __forceinline__ void tma_load_2d(uint32_t dst, const CUtensorMap* map, int c0, int c1, uint32_t bar) {
  asm volatile("cp.async.bulk.tensor.2d.shared::cluster.global.mbarrier::complete_tx::bytes [%0], [%1, {%3, %4}], [%2];"
               ::"r"(dst), "l"((uint64_t)map), "r"(bar), "r"(c0), "r"(c1) : "memory");
}
__device__ __forceinline__ void tma_load_2d_mc(uint32_t dst, const CUtensorMap* map, int c0, int c1, uint32_t bar, uint16_t mask) {
  asm volatile("cp.async.bulk.tensor.2d.shared::cluster.global.mbarrier::complete_tx::bytes.multicast::cluster [%0], [%1, {%3, %4}], [%2], %5;"
               ::"r"(dst), "l"((uint64_t)map), "r"(bar), "r"(c0), "r"(c1), "h"(mask) : "memory");
}
__device__ __forceinline__ void tma_prefetch_2d(const CUtensorMap* map, int c0, int c1) {
  asm volatile("cp.async.bulk.prefetch.tensor.2d.L2.global [%0, {%1, %2}];" ::"l"((uint64_t)map), "r"(c0), "r"(c1) : "memory");
}
__device__ __forceinline__ void bulk_load(uint32_t dst, const void* src, uint32_t bytes, uint32_t bar) {
  asm volatile("cp.async.bulk.shared::cluster.global.mbarrier::complete_tx::bytes [%0], [%1], %2, [%3];"
               ::"r"(dst), "l"((uint64_t)src), "r"(bytes), "r"(bar) : "memory");
}
__device__ __forceinline__ void bulk_store(void* dst, uint32_t src, uint32_t bytes) {
  asm volatile("cp.async.bulk.global.shared::cta.bulk_group [%0], [%1], %2;" ::"l"((uint64_t)dst), "r"(src), "r"(bytes) : "memory");
}
__device__ __forceinline__ void bulk_prefetch(const void* src, uint32_t bytes) {
  asm volatile("cp.async.bulk.prefetch.L2.global [%0], %1;" ::"l"((uint64_t)src), "r"(bytes) : "memory");
}
__device__ __forceinline__ void tma_reduce_add_2d(const CUtensorMap* map, int c0, int c1, uint32_t src) {
  asm volatile("cp.reduce.async.bulk.tensor.2d.global.shared::cta.add.tile.bulk_group [%0, {%1, %2}], [%3];"
               ::"l"((uint64_t)map), "r"(c0), "r"(c1), "r"(src) : "memory");
}
__device__ __forceinline__ void bulk_commit() { asm volatile("cp.async.bulk.commit_group;" ::: "memory"); }
__device__ __forceinline__ void bulk_wait_all() { asm volatile("cp.async.bulk.wait_group 0;" ::: "memory"); }
__device__ __forceinline__ void bulk_wait_read() { asm volatile("cp.async.bulk.wait_group.read 0;" ::: "memory"); }
__device__ __forceinline__ void fence_async_smem() { asm volatile("fence.proxy.async.shared::cta;" ::: "memory"); }
__device__ __forceinline__ void fence_async_all() { asm volatile("fence.proxy.async.global;" ::: "memory"); }
__device__ __forceinline__ void cluster_arrive() { asm volatile("barrier.cluster.arrive.relaxed.aligned;" ::: "memory"); }
__device__ __forceinline__ void cluster_wait() { asm volatile("barrier.cluster.wait.aligned;" ::: "memory"); }
__device__ __forceinline__ void prefetch_map(const CUtensorMap* m) { asm volatile("prefetch.tensormap [%0];" ::"l"((uint64_t)m) : "memory"); }
__device__ __forceinline__ uint32_t cluster_rank() { uint32_t r; asm volatile("mov.u32 %0, %%cluster_ctarank;" : "=r"(r)); return r; }
__device__ __forceinline__ uint32_t smid() { uint32_t r; asm volatile("mov.u32 %0, %%smid;" : "=r"(r)); return r; }
__device__ __forceinline__ bool elect_one() {
  uint32_t p;
  asm volatile("{\n.reg .pred P;\nelect.sync _|P, 0xffffffff;\nselp.b32 %0, 1, 0, P;\n}\n" : "=r"(p));
  return p != 0;
}
__device__ __forceinline__ void wg_fence() { asm volatile("wgmma.fence.sync.aligned;" ::: "memory"); }
__device__ __forceinline__ void wg_commit() { asm volatile("wgmma.commit_group.sync.aligned;" ::: "memory"); }
template <int N> __device__ __forceinline__ void wg_wait() { asm volatile("wgmma.wait_group.sync.aligned %0;" ::"n"(N) : "memory"); }
template <int ID, int N> __device__ __forceinline__ void bar_sync() { asm volatile("bar.sync %0, %1;" ::"n"(ID), "n"(N) : "memory"); }
template <int ID, int N> __device__ __forceinline__ void bar_arrive() { asm volatile("bar.arrive %0, %1;" ::"n"(ID), "n"(N) : "memory"); }
template <int R> __device__ __forceinline__ void reg_inc() { asm volatile("setmaxnreg.inc.sync.aligned.u32 %0;" ::"n"(R)); }
template <int R> __device__ __forceinline__ void reg_dec() { asm volatile("setmaxnreg.dec.sync.aligned.u32 %0;" ::"n"(R)); }
__device__ __forceinline__ unsigned ld_acquire(const unsigned* p) { unsigned v; asm volatile("ld.acquire.gpu.global.u32 %0, [%1];" : "=r"(v) : "l"(p) : "memory"); return v; }
__device__ __forceinline__ void st_release(unsigned* p, unsigned v) { asm volatile("st.release.gpu.global.u32 [%0], %1;" ::"l"(p), "r"(v) : "memory"); }
__device__ __forceinline__ void red_release_add(unsigned* p, unsigned v) { asm volatile("red.release.gpu.global.add.u32 [%0], %1;" ::"l"(p), "r"(v) : "memory"); }
__device__ __forceinline__ void wait_ge(const unsigned* p, unsigned target) {
  int tries = 0;
#pragma unroll 1
  while ((int)(ld_acquire(p) - target) < 0) {
    __nanosleep(40);
    if (++tries > (1 << 18)) break;
  }
}
__device__ __forceinline__ uint32_t lds32(uint32_t a) { uint32_t v; asm volatile("ld.shared.u32 %0, [%1];" : "=r"(v) : "r"(a) : "memory"); return v; }
__device__ __forceinline__ uint4 lds128(uint32_t a) { uint4 v; asm volatile("ld.shared.v4.u32 {%0,%1,%2,%3}, [%4];" : "=r"(v.x), "=r"(v.y), "=r"(v.z), "=r"(v.w) : "r"(a) : "memory"); return v; }
__device__ __forceinline__ float4 lds128f(uint32_t a) { float4 v; asm volatile("ld.shared.v4.f32 {%0,%1,%2,%3}, [%4];" : "=f"(v.x), "=f"(v.y), "=f"(v.z), "=f"(v.w) : "r"(a) : "memory"); return v; }
__device__ __forceinline__ void sts32f(uint32_t a, float v) { asm volatile("st.shared.f32 [%0], %1;" ::"r"(a), "f"(v) : "memory"); }
__device__ __forceinline__ void sts128(uint32_t a, uint4 v) { asm volatile("st.shared.v4.u32 [%0], {%1,%2,%3,%4};" ::"r"(a), "r"(v.x), "r"(v.y), "r"(v.z), "r"(v.w) : "memory"); }
__device__ __forceinline__ void stmatrix_x4(uint32_t a, uint32_t r0, uint32_t r1, uint32_t r2, uint32_t r3) {
  asm volatile("stmatrix.sync.aligned.m8n8.x4.shared.b16 [%0], {%1,%2,%3,%4};" ::"r"(a), "r"(r0), "r"(r1), "r"(r2), "r"(r3) : "memory");
}
__device__ __forceinline__ void stmatrix_x4_trans(uint32_t a, uint32_t r0, uint32_t r1, uint32_t r2, uint32_t r3) {
  asm volatile("stmatrix.sync.aligned.m8n8.x4.trans.shared.b16 [%0], {%1,%2,%3,%4};" ::"r"(a), "r"(r0), "r"(r1), "r"(r2), "r"(r3) : "memory");
}
__device__ __forceinline__ uint32_t pack_bf16(float lo, float hi) {
  uint32_t r; asm("cvt.rn.bf16x2.f32 %0, %1, %2;" : "=r"(r) : "f"(hi), "f"(lo)); return r;
}
__device__ __forceinline__ uint32_t bmul2(uint32_t a, uint32_t b) { uint32_t r; asm("mul.rn.bf16x2 %0, %1, %2;" : "=r"(r) : "r"(a), "r"(b)); return r; }
__device__ __forceinline__ uint32_t badd2(uint32_t a, uint32_t b) { uint32_t r; asm("add.rn.bf16x2 %0, %1, %2;" : "=r"(r) : "r"(a), "r"(b)); return r; }
__device__ __forceinline__ uint32_t ldg32(const void* p) { uint32_t v; asm volatile("ld.global.nc.u32 %0, [%1];" : "=r"(v) : "l"(p)); return v; }

__device__ __forceinline__ void tma_load_3d_mc(uint32_t dst, const CUtensorMap* map, int c0, int c1, int c2, uint32_t bar, uint16_t mask) {
  asm volatile("cp.async.bulk.tensor.3d.shared::cluster.global.mbarrier::complete_tx::bytes.multicast::cluster [%0], [%1, {%3, %4, %5}], [%2], %6;"
               ::"r"(dst), "l"((uint64_t)map), "r"(bar), "r"(c0), "r"(c1), "r"(c2), "h"(mask) : "memory");
}
__device__ __forceinline__ void tma_load_3d(uint32_t dst, const CUtensorMap* map, int c0, int c1, int c2, uint32_t bar) {
  asm volatile("cp.async.bulk.tensor.3d.shared::cluster.global.mbarrier::complete_tx::bytes [%0], [%1, {%3, %4, %5}], [%2];"
               ::"r"(dst), "l"((uint64_t)map), "r"(bar), "r"(c0), "r"(c1), "r"(c2) : "memory");
}
__device__ __forceinline__ void tma_store_2d(const CUtensorMap* map, int c0, int c1, uint32_t src) {
  asm volatile("cp.async.bulk.tensor.2d.global.shared::cta.tile.bulk_group [%0, {%1, %2}], [%3];"
               ::"l"((uint64_t)map), "r"(c0), "r"(c1), "r"(src) : "memory");
}
__device__ __forceinline__ void red_relaxed_add(unsigned* p, unsigned v) { asm volatile("red.relaxed.gpu.global.add.u32 [%0], %1;" ::"l"(p), "r"(v) : "memory"); }
__device__ __forceinline__ uint32_t mapa(uint32_t a, uint32_t cta) { uint32_t r; asm("mapa.shared::cluster.u32 %0, %1, %2;" : "=r"(r) : "r"(a), "r"(cta)); return r; }
__device__ __forceinline__ void st_async128(uint32_t a, uint4 v, uint32_t bar) {
  asm volatile("st.async.weak.shared::cluster.mbarrier::complete_tx::bytes.v4.b32 [%0], {%1,%2,%3,%4}, [%5];"
               ::"r"(a), "r"(v.x), "r"(v.y), "r"(v.z), "r"(v.w), "r"(bar) : "memory");
}
__device__ __forceinline__ void st_relaxed(unsigned* p, unsigned v) { asm volatile("st.relaxed.gpu.global.u32 [%0], %1;" ::"l"(p), "r"(v) : "memory"); }
__device__ __forceinline__ uint4 ldg128(const void* p) {
  uint4 v; asm volatile("ld.global.nc.L1::no_allocate.v4.u32 {%0,%1,%2,%3}, [%4];" : "=r"(v.x), "=r"(v.y), "=r"(v.z), "=r"(v.w) : "l"(p)); return v;
}
__device__ __forceinline__ uint32_t lds16(uint32_t a) { uint16_t v; asm volatile("ld.shared.u16 %0, [%1];" : "=h"(v) : "r"(a) : "memory"); return v; }
__device__ __forceinline__ float bf_lo(uint32_t v) { return __uint_as_float(v << 16); }
__device__ __forceinline__ float bf_hi(uint32_t v) { return __uint_as_float(v & 0xffff0000u); }

template <class F>
__device__ __forceinline__ void poll16(const unsigned* p, uint32_t slot, F ok) {
#pragma unroll 1
  for (int k = 0; k < (1 << 18); k++) {
    asm volatile("cp.async.cg.shared.global [%0], [%1], 16;\ncp.async.commit_group;" ::"r"(slot + (k & 3) * 16), "l"(p) : "memory");
    if (k < 3) { __nanosleep(PSLP); continue; }
    asm volatile("cp.async.wait_group 3;" ::: "memory");
    if (ok(lds128(slot + ((k + 1) & 3) * 16))) break;
  }
}

#define BAR_FULL(s)  (bars + 8 * (s))
#define BAR_EMPTY(s) (bars + 8 * (5 + (s)))
#define BAR_KV(i)    (bars + 8 * (10 + (i)))
#define BAR_XFULL(g) (bars + 8 * (15 + (g)))
#define BAR_U(c)     (bars + 8 * (17 + (c)))
#define BAR_TAB(c)   (bars + 8 * (22 + (c)))
#define BAR_XFREE    (bars + 8 * 27)
#define BAR_EPOCH    (bars + 8 * 28)
#define BAR_EPI(g)   (bars + 8 * (29 + (g)))
#define EPOCH_WORD   (bars + 8 * 31)
#define NB_G0 2
#define NB_G1 3
#define NB_AUX 4
#define NB_PRE 5
#define NB_PUB 6
#define NB_T0 7
#define NB_PFULL 8
#define NB_PFREE 9

__device__ __forceinline__ void frag_load(uint32_t (&f)[16], uint32_t hp) {
#pragma unroll
  for (int j = 0; j < 4; j++) {
    f[4 * j + 0] = lds32(hp + 32 * j);
    f[4 * j + 1] = lds32(hp + 32 * j + 256);
    f[4 * j + 2] = lds32(hp + 32 * j + 16);
    f[4 * j + 3] = lds32(hp + 32 * j + 272);
  }
}
template <int B>
__device__ __forceinline__ void conv_issue(float* acc, uint32_t (&f)[16], uint32_t desc) {
  wg_fence();
#pragma unroll
  for (int j = 0; j < 4; j++) wgmma_rs<128 - 16 * B>(acc, f[4 * j], f[4 * j + 1], f[4 * j + 2], f[4 * j + 3], desc, 32 * B + 2 * j, B >= 2 || j != 0);
  wg_commit();
}
template <int B>
__device__ __forceinline__ void conv_batch(float* acc, uint32_t (&f)[16], uint32_t hp, uint32_t desc) {
  frag_load(f, hp + 512 * B);
  conv_issue<B>(acc, f, desc);
}
template <int N>
__device__ __forceinline__ void conv_rename(float* acc) {
#pragma unroll
  for (int i = 0; i < N / 2; i++) { float t; asm volatile("mov.b32 %0, %1;" : "=f"(t) : "f"(acc[i]) : "memory"); acc[i] = t; }
}
template <int G0, int G1>
__device__ __forceinline__ void conv_dump(const float* X, const float* Y, const uint32_t (&pw)[2], bool late) {
#pragma unroll
  for (int G = G0; G < G1; G++) {
#pragma unroll
    for (int j = 0; j < 2; j++) {
      float v = X[4 * G + j];
      if (G < 15) v += X[4 * G + 6 + j];
      if (G < 13) v += Y[4 * G + j] + Y[4 * G + 6 + j];
      else if (G < 14) v += Y[4 * G + j];
      if (G != 0 || !late) sts32f(pw[j] - 512 * G, v);
    }
  }
}
template <int B>
__device__ __forceinline__ void conv_round(float* X, float* Y, uint32_t (&fx)[16], uint32_t (&fy)[16], uint32_t hp, uint32_t desc,
                                           const uint32_t (&pw)[2], bool late) {
  wg_wait<B < 8 ? 1 : 0>();
  conv_rename<144 - 16 * B>((B & 1) ? X : Y);
  if constexpr (B < 7) conv_batch<B + 1>((B & 1) ? X : Y, (B & 1) ? fx : fy, hp, desc);
  if constexpr (B == DI) bar_sync<NB_PFREE, 224>();
  if constexpr (B >= DI) conv_dump<16 - 2 * B, B == DI ? 16 : 18 - 2 * B>(X, Y, pw, late);
}
#define CT(i) do {} while (0)
__device__ __forceinline__ void conv_channel(uint32_t hp, uint32_t desc, const uint32_t (&pw)[2], bool late, uint32_t tr) {
  CT(25);
  float X[64], Y[56];
  uint32_t fx[16], fy[16];
  conv_batch<0>(X, fx, hp, desc);
  CT(46);
  conv_batch<1>(Y, fy, hp, desc);
  CT(47);
  conv_round<1>(X, Y, fx, fy, hp, desc, pw, late);
  CT(48);
  conv_round<2>(X, Y, fx, fy, hp, desc, pw, late);
  CT(49);
  uint32_t f2[16], f3[16];
  frag_load(f2, hp + 512 * 4);
  wg_wait<1>(); conv_rename<96>(X); conv_issue<4>(X, f2, desc);
  CT(57);
  frag_load(fx, hp + 512 * 5);
  bar_sync<NB_PFREE, 224>();
  CT(58);
  conv_dump<10, 16>(X, Y, pw, late);
  frag_load(f3, hp + 512 * 6);
  wg_wait<1>(); conv_rename<80>(Y); conv_issue<5>(Y, fx, desc);
  CT(59);
  frag_load(fy, hp + 512 * 7);
  conv_dump<8, 10>(X, Y, pw, late);
  wg_wait<1>(); conv_rename<64>(X); conv_issue<6>(X, f3, desc);
  CT(60);
  conv_dump<6, 8>(X, Y, pw, late);
  wg_wait<1>(); conv_rename<48>(Y); conv_issue<7>(Y, fy, desc);
  CT(61);
  conv_dump<4, 6>(X, Y, pw, late);
  conv_round<7>(X, Y, fx, fy, hp, desc, pw, late);
  CT(62);
  conv_round<8>(X, Y, fx, fy, hp, desc, pw, late);
  CT(63);
}

#define KERNEL_END() do { cluster_arrive(); cluster_wait(); } while (0)

struct Params {
  const __nv_bfloat16 *hr, *hi, *shift_k, *ssm_k, *q, *ssm_D;
};

__device__ __forceinline__ void fin_phase(const CUtensorMap* mT, const CUtensorMap* mQ, const CUtensorMap* mO, uint32_t base, uint32_t bars,
                                          int i, int lane, int cta, bool leader) {
  const uint32_t qb = base + OFF_PART + 20992 + i * 4096, zb = base + OFF_PART + (i < 4 ? i * 4096 : 41984);
  const int tk = cta >> 2, cg = (cta & 3) * 5 + i;
  if (leader) {
    const unsigned target = (lds32(EPOCH_WORD) + 1) * 32;
    if (i == 0) STAMP(44);
    wait_ge(&g_cnt[(8 + (i & 4) + (cta & 3)) * 32], target);
    if (i == 4) STAMP(43);
    if (i == 3) STAMP(50);
    fence_async_all();
    tma_load_2d(zb, mT, (31 - tk) * 64, 640 + cg * 32, BAR_U(i));
  }
  __syncwarp();
  mbar_wait(BAR_U(i), 1);
  if (leader && i >= 3) STAMP(48 + i);
  const int r = lane & 7, m = lane >> 3;
  const uint32_t qa = qb + r * 64 + ((m ^ (r >> 1)) << 4);
  const uint32_t za = zb + lane * 128 + ((7 ^ r ^ ((tk & 1) ^ 1)) << 4);
  uint32_t q[32], z[32];
#pragma unroll
  for (int g = 0; g < 8; g++) {
    asm volatile("ldmatrix.sync.aligned.m8n8.x4.shared.b16 {%0,%1,%2,%3}, [%4];" : "=r"(q[4 * g]), "=r"(q[4 * g + 1]), "=r"(q[4 * g + 2]), "=r"(q[4 * g + 3]) : "r"(qa + g * 512) : "memory");
    asm volatile("ldmatrix.sync.aligned.m8n8.x4.trans.shared.b16 {%0,%1,%2,%3}, [%4];" : "=r"(z[4 * g]), "=r"(z[4 * g + 1]), "=r"(z[4 * g + 2]), "=r"(z[4 * g + 3]) : "r"(za ^ (g << 4)) : "memory");
  }
#pragma unroll
  for (int g = 0; g < 8; g++)
    stmatrix_x4(qa + g * 512, bmul2(q[4 * g], z[4 * g]), bmul2(q[4 * g + 1], z[4 * g + 1]), bmul2(q[4 * g + 2], z[4 * g + 2]), bmul2(q[4 * g + 3], z[4 * g + 3]));
  fence_async_smem();
  __syncwarp();
  if (leader) {
    if (i >= 3) STAMP(50 + i);
    asm volatile("cp.async.bulk.tensor.3d.global.shared::cta.tile.bulk_group [%0, {%1, %2, %3}], [%4];"
                 ::"l"((uint64_t)mO), "r"(0), "r"(tk * 64), "r"(20 + cg), "r"(qb) : "memory");
    bulk_commit();
    bulk_wait_read();
    if (i == 3) STAMP(21);
    if (i == 4) STAMP(22);
  }
  __syncwarp();
}

__device__ __forceinline__ void pre_phase(uint32_t base, uint32_t bars, int wt, int cta) {
  const int rg = wt >> 4, cp = wt & 15;
  const int uk = (7 - rg) ^ (((cta >> 2) & 1) ^ 1);
  uint32_t sk = base + OFF_SK + cp * 16;
  uint32_t ak = base + OFF_SLOT(9) + rg * 512 + cp * 4, av = base + OFF_SLOT(0) + rg * 512 + cp * 4;
  uint32_t ah = rg ? ak - 192 : base + OFF_HALO + cp * 4;
  const int hstep = rg ? -4096 : 192;
  const uint32_t ob = base + cp * 256 + ((uk ^ ((2 * cp) & 7)) << 4);
#pragma unroll 1
  for (int i = 0; i < 5; i++) {
    mbar_wait_slow(BAR_KV(i), 0);
    if (wt == 0 && i == 0) STAMP(32);
    if (wt == 0 && i == 4) STAMP(46);
    const uint4 sw = lds128(sk);
    uint32_t kk[11], kv[8];
#pragma unroll
    for (int j = 0; j < 3; j++) kk[j] = lds32(ah + j * 64);
#pragma unroll
    for (int j = 0; j < 8; j++) kk[3 + j] = lds32(ak + j * 64);
#pragma unroll
    for (int j = 0; j < 8; j++) kv[j] = lds32(av + j * 64);
    const uint32_t w0 = __byte_perm(sw.x, sw.z, 0x5410), w1 = __byte_perm(sw.x, sw.z, 0x7632);
    const uint32_t w2 = __byte_perm(sw.y, sw.w, 0x5410), w3 = __byte_perm(sw.y, sw.w, 0x7632);
#pragma unroll
    for (int j = 0; j < 8; j++) {
      uint32_t a = bmul2(kk[j], w3);
      a = badd2(a, bmul2(kk[j + 1], w2));
      a = badd2(a, bmul2(kk[j + 2], w1));
      a = badd2(a, bmul2(kk[j + 3], w0));
      kv[j] = bmul2(a, kv[j]);
    }
    if (i) bar_sync<NB_PRE, 128>();
    if (i == 2) bar_arrive<NB_T0, 192>();
    const uint32_t o0 = ob + OFF_SLOT(i ? i - 1 : 10);
    sts128(o0, make_uint4(__byte_perm(kv[7], kv[6], 0x5410), __byte_perm(kv[5], kv[4], 0x5410), __byte_perm(kv[3], kv[2], 0x5410), __byte_perm(kv[1], kv[0], 0x5410)));
    sts128((o0 + 128) ^ 16, make_uint4(__byte_perm(kv[7], kv[6], 0x7632), __byte_perm(kv[5], kv[4], 0x7632), __byte_perm(kv[3], kv[2], 0x7632), __byte_perm(kv[1], kv[0], 0x7632)));
    if ((i & 3) == 0) fence_async_smem();
    if (i == 0) bar_arrive<NB_PUB, 160>();
    sk += 256; ak -= 4096; ah += hstep; av += 4096;
  }
}

__global__ void __cluster_dims__(2, 1, 1) __launch_bounds__(NTHREADS, 1)
fused_kernel(const __grid_constant__ Params p, const __grid_constant__ CUtensorMap mX, const __grid_constant__ CUtensorMap mHr, const __grid_constant__ CUtensorMap mHi,
             const __grid_constant__ CUtensorMap mCr, const __grid_constant__ CUtensorMap mCi,
             const __grid_constant__ CUtensorMap mT, const __grid_constant__ CUtensorMap mKh,
             const __grid_constant__ CUtensorMap mK, const __grid_constant__ CUtensorMap mV,
             const __grid_constant__ CUtensorMap mOut, const __grid_constant__ CUtensorMap mQ, const __grid_constant__ CUtensorMap mO) {
  extern __shared__ __align__(1024) unsigned char smem_raw[];
  const uint32_t base = smem_u32(smem_raw);
  const uint32_t bars = base + OFF_BAR;
  const int tid = threadIdx.x;
  const int cta = blockIdx.x, cid = blockIdx.x >> 1;
  const uint32_t rank = cta & 1;
  const CUtensorMap* mC = rank ? &mCi : &mCr;
  int tb, db;
  {
    const int t = cid - 4, q7 = ((t - 32) * 37) >> 8;
    int v = t < 32 ? (t & 7) * 8 + (t >> 3) : (t - 31 - 7 * q7) * 8 + 4 + q7;
    v = t < 0 ? 4 + cid : v;
    tb = v >> 2; db = v & 3;
  }
  if (tid >= 480 && elect_one()) {
#pragma unroll 1
    for (int it = 0; it < XOWN; it++) {
      const uint32_t sa = base + it * STAGE_BYTES, bf = BAR_FULL(it);
      mbar_init(bf, 1);
      asm volatile("fence.mbarrier_init.release.cluster;" ::: "memory");
      mbar_expect_tx(bf, STAGE_BYTES);
      tma_load_2d(sa, mC, it * 64, tb * 128, bf);
      tma_load_3d(sa + A_BYTES, &mX, 0, it * 64, db * 5, bf);
      tma_load_3d(sa + A_BYTES + 10240, &mX, 0, it * 64 + 32, db * 5, bf);
      if (it == 0) VAL(58, clock64() - c_entry);
    }
    VAL(62, clock64() - c_entry);
  }
  const int warp = __shfl_sync(0xffffffffu, tid >> 5, 0), lane = tid & 31;
  const int wgi = warp >> 2, w = warp & 3, wt = tid & 127;
  const int odd = db & 1;
  const int ch0 = (cta >> 5) * 160 + (cta & 31);
  const bool leader = elect_one();
  if (leader && warp < 15) {
#pragma unroll 1
    for (int b = XOWN + 2 * warp; b < min(XOWN + 2 + 2 * warp, 31); b++) {
      mbar_init(bars + 8 * b, (b >= 5 && b < 10) ? 4 : (b >= 22 && b < 28 ? 2 : 1));
      uint32_t by = 8192 + 960 + 1280;
      if (b >= 11) by = 8192;
      if (b >= 15) by = 10240;
      if (b >= 17) by = 4096;
      if (b >= 10 && b < 22) mbar_expect_tx(bars + 8 * b, by);
    }
    asm volatile("fence.mbarrier_init.release.cluster;" ::: "memory");
  }
  __syncwarp();
  cluster_arrive();
  if (warp < 15) cluster_wait();
  if (wgi == 3) {
    reg_dec<R_AUX>();
    if (warp == 15) {
      if (leader) { VAL(57, clock64() - c_entry); STAMPC(30); VAL(55, smid()); VAL(56, tb * 4 + db); }
      int s = XOWN % STAGES, ph = XOWN < STAGES;
      cluster_wait();
      if (leader) VAL(59, clock64() - c_entry);
#pragma unroll 1
      for (int it = XOWN; it < 32; it++) {
        const uint32_t sa = base + s * STAGE_BYTES, bf = BAR_FULL(s);
        if (it >= STAGES) mbar_wait(BAR_EMPTY(s), ph);
        if (leader) {
          mbar_expect_tx(bf, STAGE_BYTES);
          tma_load_2d(sa, mC, it * 64, tb * 128, bf);
          tma_load_3d_mc(sa + A_BYTES + rank * 10240, &mX, 0, it * 64 + rank * 32, db * 5, bf, 3);
          const unsigned e = it - G_KV;
          if (e < 10) tma_load_3d(base + OFF_SLOT((e & 1) ? e >> 1 : 9 - (e >> 1)), (e & 1) ? &mV : &mK, 0, (cta >> 2) * 64, (cta & 3) * 5 + (e >> 1), BAR_KV(e >> 1));
          if (e == 0) {
            tma_load_3d(base + OFF_HALO, &mKh, 0, (cta >> 2) * 64 - 3, (cta & 3) * 5, BAR_KV(0));
            bulk_load(base + OFF_SK, p.shift_k + (cta & 3) * 640, 1280, BAR_KV(0));
          }
          if ((unsigned)(it - G_T) < 4) bulk_prefetch(p.ssm_k + (size_t)(ch0 + 32 * (it - G_T + 1)) * 2048, 4096);
          if ((unsigned)(it - G_Q) < 2) bulk_prefetch(p.q + (size_t)(cta * 2 + it - G_Q) * 8 * 640, 8 * 1280);
          if (it == G_H) bulk_prefetch((rank ? p.hi : p.hr) + (size_t)cid * 10 * 640, 10 * 1280);
        }
        if (++s == STAGES) { s = 0; ph ^= 1; }
      }
      if (leader) {
        const CUtensorMap* mH = rank ? &mHi : &mHr;
        const int kb5 = (db >> 1) * 5;
        unsigned char* ub = g_u + (size_t)(tb * 2 + rank) * 10 * A_BYTES;
        unsigned* flags = g_flag + (tb * 2 + rank) * 32;
        unsigned tag = 0, seen = 0;
        mbar_wait(BAR_EPOCH, 0);
        tag = (lds32(EPOCH_WORD) + 1) * 6;
#pragma unroll 1
        for (int i = 7 - NBE; i < 15; i++) {
          const int j = i < 7 ? i - (7 - NBE) : i - 5;
          const int kb = (j < 5) ? kb5 + (odd ? (j < 2 ? j + 3 : (j == 2 ? 2 : j - 3)) : j) : j - kb5;
          s = (32 + j) % STAGES;
          const uint32_t sa = base + s * STAGE_BYTES, bf = BAR_FULL(s);
          if (i >= 7) {
            const unsigned need = j < 5 ? 1u << (db ^ 1) : (j < 7 ? 15 - (2 << ((db ^ 2) & 2)) : 15);
            if ((seen & need) != need) {
#pragma unroll 1
              for (int tries = 0; tries < (1 << 18); tries++) {
                uint4 f;
                asm volatile("ld.acquire.gpu.global.v4.u32 {%0,%1,%2,%3}, [%4];" : "=r"(f.x), "=r"(f.y), "=r"(f.z), "=r"(f.w) : "l"(flags) : "memory");
                seen = (f.x == tag) | (f.y == tag) << 1 | (f.z == tag) << 2 | (f.w == tag) << 3;
                if ((seen & need) == need) break;
              }
              fence_async_all();
            }
            if (i == 7) STAMP(4);
            if (i == 12) STAMP(5);
          }
          if (i < 7 || j >= NBE) {
            mbar_wait(BAR_EMPTY(s), ((32 + j) / STAGES & 1) ^ 1);
            mbar_expect_tx(bf, B_BYTES + (j < 2 ? 0 : (j == 2 ? 8192 : A_BYTES)));
            tma_load_2d(sa + A_BYTES, mH, kb * 64, db * 160 + rank * 80, bf);
            tma_load_2d(sa + A_BYTES + 10240, mH, kb * 64, db * 160 + (rank ^ 1) * 80, bf);
          }
          if (i >= 7) {
            const uint32_t off = i == 7 ? (odd ^ 1) * 4096 : 0, sz = i == 7 ? 4096 : 8192;
            bulk_load(sa + off, ub + kb * A_BYTES + off, sz, bf);
            bulk_load(sa + off + 8192, ub + kb * A_BYTES + off + 8192, sz, bf);
          }
        }
      }
      __syncwarp();
    } else {
      unsigned target = 0;
      if (w == 1 && leader) {
        target = atomicAdd(&g_ticket, 1u) / NCTA;
        asm volatile("st.shared.u32 [%0], %1;" ::"r"(EPOCH_WORD), "r"(target) : "memory");
        mbar_arrive(BAR_EPOCH);
        target = (target + 1) * 32;
      }
      const uint32_t part = base + OFF_PART;
      const int tu = lane + w * 16;
      const uint32_t s0 = (wt * 8 ^ (((wt >> 2) & 3) << 3) ^ (((wt >> 2) & 1) << 2)) * 4;
      const uint32_t uo = ((255 - wt) ^ (((255 - wt) >> 3) & 1)) << 4;
      const __nv_bfloat16* hsrc = p.ssm_k + (size_t)ch0 * 2048 + tu * 8;
      mbar_wait_slow(BAR_KV(0), 0);
#pragma unroll 1
      for (int hs = -2; hs < 5; hs++) {
        const bool tab = hs < 3 && w != 1;
        uint4 hv[4];
        uint32_t hpv[4];
        hpv[0] = 0;
        if (tab) {
#pragma unroll
          for (int i = 0; i < 4; i++) {
            hv[i] = ldg128(hsrc + i * 512);
            if (lane == 0 && (i || wt)) hpv[i] = ldg32(hsrc + i * 512 - 2);
          }
        }
        hsrc += 32 * 2048;
        const uint32_t dd = (uint32_t)__bfloat16_as_ushort(p.ssm_D[ch0 + 32 * max(hs, 0)]) * 0x10001u;
        asm volatile("bar.sync %0, %1;" ::"r"(hs > -2 ? NB_PFULL : (w == 1 ? NB_PUB : NB_T0)), "r"(hs > -2 ? 224 : (w == 1 ? 160 : 192)) : "memory");
        if (hs >= 0) {
          uint32_t y[3][4];
#pragma unroll
          for (int k = 0; k < 3; k++) {
            if (k < 2 || w < 2) {
              const uint32_t pa = part + s0 + k * 3072;
              float4 lo = lds128f(pa), hi = lds128f(pa ^ 16);
              if (k || wt >= 8) {
                const float4 l2 = lds128f(pa + 8192), h2 = lds128f((pa ^ 16) + 8192);
                lo.x += l2.x; lo.y += l2.y; lo.z += l2.z; lo.w += l2.w;
                hi.x += h2.x; hi.y += h2.y; hi.z += h2.z; hi.w += h2.w;
              }
              y[k][0] = pack_bf16(lo.x, lo.y); y[k][1] = pack_bf16(lo.z, lo.w); y[k][2] = pack_bf16(hi.x, hi.y); y[k][3] = pack_bf16(hi.z, hi.w);
            }
          }
          bar_arrive<NB_PFREE, 224>();
#pragma unroll
          for (int k = 0; k < 3; k++) {
            if (k < 2 || w < 2) {
              const uint32_t ua = base + u_off(hs) + uo - k * 1536;
              const uint4 u = lds128(ua);
              sts128(ua, make_uint4(badd2(y[k][0], bmul2(__byte_perm(u.w, 0, 0x1032), dd)), badd2(y[k][1], bmul2(__byte_perm(u.z, 0, 0x1032), dd)),
                                    badd2(y[k][2], bmul2(__byte_perm(u.y, 0, 0x1032), dd)), badd2(y[k][3], bmul2(__byte_perm(u.x, 0, 0x1032), dd))));
            }
          }
          fence_async_smem();
        } else if (w == 1) {
          if (leader) {
            STAMP(hs == -2 ? 33 : 47);
#pragma unroll 1
            for (int i = hs + 2; i < 4 * hs + 9; i++) tma_store_2d(&mT, (31 - (cta >> 2)) * 64, (cta & 3) * 160 + 32 * i, base + OFF_SLOT(i ? i - 1 : 10));
            bulk_commit();
            bulk_wait_all();
            red_relaxed_add(&g_cnt[(4 * hs + 8 + (cta & 3)) * 32], 1u);
            STAMP(hs == -2 ? 34 : 48);
          }
          __syncwarp();
        }
        if (RFAST ? hs == -1 : hs > -2) bar_arrive<NB_PFREE, 224>();
        if (tab) {
          const uint32_t a = base + OFF_HT + ((hs & 1) ^ 1) * HT_BYTES + 32 + tu * 16;
          if (wt < 4) sts128(a - 32 + (wt >> 1) * (HC_BYTES - 32), make_uint4(0, 0, 0, 0));
#pragma unroll
          for (int i = 0; i < 4; i++) {
            const uint32_t up = __shfl_up_sync(0xffffffffu, hv[i].w, 1);
            if (lane) hpv[i] = up;
            sts128(a + i * 1024, hv[i]);
            sts128(a + i * 1024 + HC_BYTES, make_uint4(__byte_perm(hpv[i], hv[i].x, 0x5432), __byte_perm(hv[i].x, hv[i].y, 0x5432),
                                                       __byte_perm(hv[i].y, hv[i].z, 0x5432), __byte_perm(hv[i].z, hv[i].w, 0x5432)));
          }
          __syncwarp();
          if (leader) mbar_arrive(BAR_TAB(hs + 2));
        }
        if (hs >= 0) bar_sync<NB_AUX, 96>();
        if (w == 1) {
          if (hs < 0) {
            asm volatile("st.shared.v2.u32 [%0], {%1, %1};" ::"r"(base + u_off(hs + 2) + 4096 + lane * 8), "r"(0) : "memory");
            asm volatile("st.shared.v2.u32 [%0], {%1, %1};" ::"r"(base + u_off(2 * hs + 4) + 4096 + lane * 8), "r"(0) : "memory");
            fence_async_smem();
            __syncwarp();
          }
          if (leader) {
            if (hs < 0) {
              wait_ge(&g_cnt[(4 * hs + 8 + (cta >> 5)) * 32], target);
              STAMP(hs == -2 ? 35 : 49);
            }
            if (hs >= 0) {
              if (hs == 4) STAMP(20);
              bulk_store(g_t + (size_t)(640 + ch0 + 32 * hs) * 4096, base + u_off(hs), 4096);
              bulk_commit();
              bulk_wait_all();
              if (hs >= 3) red_relaxed_add(&g_cnt[(4 * hs - 4 + (cta >> 5)) * 32], 1u);
              if (hs == 4) STAMP(42);
            }
            if (hs >= 3) {
#pragma unroll 1
              for (int i = 3 * hs - 9; i < 2 * hs - 3; i++) {
                mbar_expect_tx(BAR_U(i), 8192);
                tma_load_3d(base + OFF_PART + 20992 + i * 4096, &mQ, 0, (cta >> 2) * 64, (cta & 3) * 5 + i, BAR_U(i));
              }
            }
            if (hs < 2) {
              fence_async_all();
#pragma unroll 1
              for (int c = hs < 0 ? hs + 2 : hs + 3; c <= (hs == -2 ? 0 : hs + 3); c++)
                bulk_load(base + u_off(c), g_t + (size_t)(ch0 + 32 * c) * 4096, 4096, BAR_U(c));
            }
          }
          __syncwarp();
        }
      }
      __syncwarp();
    }
  } else if (wgi == 0) {
    reg_inc<R_CONV>();
    pre_phase(base, bars, wt, cta);
    if (wt == 0) STAMP(45);
    bar_arrive<NB_PFULL, 224>();
    const int g = lane >> 2, tig = lane & 3, ph = w & 1, lg = w >> 1;
    const int x00 = 64 * lg + 8 * ph + g + 2 * tig + 1;
    const uint32_t hp = base + OFF_HT + ((x00 & 1) ? HC_BYTES + 2 * (x00 + 1) : 2 * x00);
    const bool late = lg && tig < 2;
    uint32_t pw[2];
#pragma unroll
    for (int j = 0; j < 2; j++) {
      const int t = 16 * (127 + 4 * lg) - 32 * tig - 16 * j + 8 * ph + g;
      const int sw = t ^ (((t >> 5) & 3) << 3) ^ (((t >> 5) & 1) << 2);
      pw[j] = base + OFF_PART + lg * 8192 + sw * 4;
    }
#pragma unroll 1
    for (int c = 0; c < 5; c++) {
      mbar_wait_slow(BAR_TAB(c), 0);
      mbar_wait_slow(BAR_U(c), 0);
      if (wt == 0) { STAMP(10 + 2 * c); ITC(128 + 2 * c); }
      conv_channel(hp + ((c & 1) ^ 1) * HT_BYTES, (uint32_t)mkdesc(base + u_off(c), 16, 256, 3), pw, late, wt == 0 && c == CTRC ? bars + 256 : 0);
      if (wt == 0) { STAMP(11 + 2 * c); ITC(129 + 2 * c); }
      bar_arrive<NB_PFULL, 224>();
    }
    if (wt == 0) mbar_arrive(BAR_KV(1));
    bar_sync<NB_PFREE, 224>();
  } else {
    reg_dec<R_GEMM>();
    const int wg = wgi - 1;
    float acc[80];
    int s = 0, ph = 0;
    uint32_t pe = 0;
#pragma unroll 1
    for (int it = 0; it < 32; it++) {
      mbar_wait(BAR_FULL(s), ph);
      const uint32_t sa = base + s * STAGE_BYTES + wg * 8192, sb = base + s * STAGE_BYTES + A_BYTES;
      const uint64_t da = mkdesc(sa, 16, 1024, 1), db_ = mkdesc(sb, 2048, 512, 2);
#pragma unroll
      for (int i = 0; i < 80; i++) asm volatile("" : "+f"(acc[i])::"memory");
      wg_fence();
      wgmma_ss_tb160(acc, da, db_, it != 0);
      wgmma_ss_tb160(acc, da + 2, db_ + 64, 1);
      wgmma_ss_tb160(acc, da + 4, db_ + 640, 1);
      wgmma_ss_tb160(acc, da + 6, db_ + 704, 1);
      wg_commit();
      wg_wait<0>();
      if (wt < 2) mbar_arrive_cta(BAR_EMPTY(s), wt);
      if (++s == STAGES) { s = 0; ph ^= 1; }
    }
#pragma unroll
    for (int i = 0; i < 80; i++) asm volatile("" : "+f"(acc[i])::"memory");
    if (wt == 0) STAMP(wg ? 38 : 2);
    if (wt == 0) ITC(wg * 64 + 42);
    const int m = lane >> 3, i8 = lane & 7;
    {
      const int row = 16 * w + 8 * (m & 1) + i8;
      const uint32_t ad0 = base + (32 % STAGES) * STAGE_BYTES + wg * 8192 + row * 64 + (((m >> 1) ^ ((row >> 1) & 3)) << 4);
#pragma unroll
      for (int lc = 0; lc < 5; lc++) {
        const int e0 = lc, e1 = lc == 0 ? 5 : lc - 1;
        const uint32_t ad = ad0 + (odd ? (e1 >> 1) * STAGE_BYTES + (e1 & 1) * 4096 : (e0 >> 1) * STAGE_BYTES + (e0 & 1) * 4096);
#pragma unroll
        for (int h = 0; h < 2; h++) {
          const int G = lc * 4 + h * 2;
          stmatrix_x4(ad ^ (h * 32), pack_bf16(acc[4 * G], acc[4 * G + 1]), pack_bf16(acc[4 * G + 2], acc[4 * G + 3]),
                      pack_bf16(acc[4 * G + 4], acc[4 * G + 5]), pack_bf16(acc[4 * G + 6], acc[4 * G + 7]));
        }
      }
      if (leader && warp == 4) STAMP(36);
      fence_async_smem();
      asm volatile("bar.sync %0, 128;" ::"r"(NB_G0 + wg) : "memory");
      if (leader && warp == 4) STAMP(37);
      if (leader && w < 3) {
        const uint32_t off = wg * 8192 + (w == 2 ? odd * 4096 : 0);
        bulk_store(g_u + (size_t)((tb * 2 + rank) * 10 + (db >> 1) * 5 + (odd && w < 2 ? w + 3 : w)) * A_BYTES + off,
                   base + (32 % STAGES + w) * STAGE_BYTES + off, w == 2 ? 4096 : 8192);
        bulk_commit();
        if (warp == 4) STAMP(23);
      }
      __syncwarp();
    }
#pragma unroll 1
    for (int it = 32; it < 42 - NSPL; it++) {
      if (it == 32 + CPRI) mbar_wait(BAR_KV(1), 1);
      mbar_wait(BAR_FULL(s), ph);
      const uint32_t sa = base + s * STAGE_BYTES + wg * 8192, sb = base + s * STAGE_BYTES + A_BYTES;
      const uint64_t da = mkdesc(sa, 16, 512, 2), db_ = mkdesc(sb, 16, 1024, 1);
#pragma unroll
      for (int i = 0; i < 80; i++) asm volatile("" : "+f"(acc[i])::"memory");
      wg_fence();
      wgmma_ss<160>(acc, da, db_, it != 32);
      wgmma_ss<160>(acc, da + 2, db_ + 2, 1);
      wgmma_ss<160>(acc, da + 256, db_ + 4, 1);
      wgmma_ss<160>(acc, da + 258, db_ + 6, 1);
      wg_commit();
      if (it == 32 + WPUB - 1 && leader && w < 3) {
        bulk_wait_all();
        red_relaxed_add(g_flag + (tb * 2 + rank) * 32 + db, 1u);
        if (warp == 4) STAMP(3);
      }
      __syncwarp();
      wg_wait<0>();
      if (wt < 2) mbar_arrive(BAR_EMPTY(s));
      if (it == 42 - STAGES && wt == 0) mbar_arrive_cta(BAR_XFREE, rank ^ 1);
      if (++s == STAGES) { s = 0; ph ^= 1; }
    }
#pragma unroll
    for (int i = 0; i < 80; i++) asm volatile("" : "+f"(acc[i])::"memory");
    if (wt == 0) STAMP(wg ? 41 : 6);
    if (wt == 0) ITC(wg * 64 + 43);
    {
      const uint32_t xw = base + ((42 - STAGES) % STAGES) * STAGE_BYTES + wg * 10240 + w * 2560, xb = xw + lane * 16;
      const uint32_t rxb = mapa(xb, rank ^ 1), rbar = mapa(BAR_XFULL(wg), rank ^ 1);
      mbar_wait(BAR_XFREE, 0);
#pragma unroll
      for (int i = 0; i < 5; i++)
        st_async128(rxb + i * 512, make_uint4(pack_bf16(acc[40 + 8 * i], acc[40 + 8 * i + 1]), pack_bf16(acc[40 + 8 * i + 2], acc[40 + 8 * i + 3]),
                                              pack_bf16(acc[40 + 8 * i + 4], acc[40 + 8 * i + 5]), pack_bf16(acc[40 + 8 * i + 6], acc[40 + 8 * i + 7])), rbar);
      if (wg == 0 && wt == 0) STAMP(40);
      const float sk = rank ? -1.f : 1.f;
      const uint32_t sr = rank ? 0u : 0x80000000u;
      mbar_wait(BAR_XFULL(wg), 0);
      if (wg == 0 && wt == 0) STAMP(28);
      uint4 r[5];
#pragma unroll
      for (int i = 0; i < 5; i++) r[i] = lds128(xb + i * 512);
      __syncwarp();
      const uint32_t ad = xw + (8 * (m & 1) + i8) * 160 + (m >> 1) * 16;
      auto comb = [&](int i, uint32_t v) {
        return pack_bf16(fmaf(acc[i], sk, __uint_as_float((v << 16) + sr)), fmaf(acc[i + 1], sk, __uint_as_float((v & 0xffff0000u) ^ sr)));
      };
#pragma unroll
      for (int i = 0; i < 5; i++) stmatrix_x4(ad + i * 32, comb(8 * i, r[i].x), comb(8 * i + 2, r[i].y), comb(8 * i + 4, r[i].z), comb(8 * i + 6, r[i].w));
      fence_async_smem();
      __syncwarp();
      if (elect_one()) {
        tma_store_2d(&mOut, db * 160 + rank * 80, tb * 128 + wg * 64 + w * 16, xw);
        bulk_commit();
        bulk_wait_read();
      }
      __syncwarp();
      if (wg == 0 && wt == 0) { STAMP(7); STAMPC(31); ITC(44); }
    }
  }
  if (warp < 4 || warp == 14) fin_phase(&mT, &mQ, &mO, base, bars, min(warp, 4), lane, cta, leader);
  asm volatile("cp.async.wait_group 0;" ::: "memory");
  KERNEL_END();
}

typedef CUresult (*PFN_encodeTiled)(CUtensorMap*, CUtensorMapDataType, cuuint32_t, void*, const cuuint64_t*, const cuuint64_t*,
                                    const cuuint32_t*, const cuuint32_t*, CUtensorMapInterleave, CUtensorMapSwizzle,
                                    CUtensorMapL2promotion, CUtensorMapFloatOOBfill);

static CUtensorMap make_map(PFN_encodeTiled enc, const void* ptr, uint64_t inner, uint64_t outer, uint32_t box_inner, uint32_t box_outer,
                            CUtensorMapSwizzle swz, CUtensorMapL2promotion prom = CU_TENSOR_MAP_L2_PROMOTION_L2_128B) {
  CUtensorMap m;
  cuuint64_t dims[2] = {inner, outer};
  cuuint64_t strides[1] = {inner * 2};
  cuuint32_t box[2] = {box_inner, box_outer};
  cuuint32_t es[2] = {1, 1};
  enc(&m, CU_TENSOR_MAP_DATA_TYPE_BFLOAT16, 2, const_cast<void*>(ptr), dims, strides, box, es, CU_TENSOR_MAP_INTERLEAVE_NONE, swz,
      prom, CU_TENSOR_MAP_FLOAT_OOB_FILL_NONE);
  return m;
}

extern "C" void kernel_launch(void* const* d_in, const int* in_sizes, int n_in, void* d_out, int out_size) {
  static PFN_encodeTiled enc = nullptr;
  static void* gt = nullptr;
  if (!enc) {
    cudaGetSymbolAddress(&gt, g_t);
    void* fp = nullptr;
    cudaDriverEntryPointQueryResult qr;
    cudaGetDriverEntryPoint("cuTensorMapEncodeTiled", &fp, cudaEnableDefault, &qr);
    enc = (PFN_encodeTiled)fp;
    cudaFuncSetAttribute(fused_kernel, cudaFuncAttributeMaxDynamicSharedMemorySize, SMEM_BYTES);
  }
  auto map3 = [&](const void* ptr, uint32_t rows, uint32_t groups, CUtensorMapSwizzle swz, int prom, uint64_t w = 1) {
    CUtensorMap m;
    cuuint64_t dims[3] = {32, 2048, 20 * w};
    cuuint64_t strides[2] = {1280 * w, 64};
    cuuint32_t box[3] = {32, rows, groups};
    cuuint32_t es[3] = {1, 1, 1};
    enc(&m, CU_TENSOR_MAP_DATA_TYPE_BFLOAT16, 3, const_cast<void*>(ptr), dims, strides, box, es, CU_TENSOR_MAP_INTERLEAVE_NONE, swz,
        (CUtensorMapL2promotion)prom, CU_TENSOR_MAP_FLOAT_OOB_FILL_NONE);
    return m;
  };
  CUtensorMap mX = map3(d_in[0], 32, 5, CU_TENSOR_MAP_SWIZZLE_64B, PR_X);
  CUtensorMap mKh = map3(d_in[6], 3, 5, CU_TENSOR_MAP_SWIZZLE_NONE, PR_K);
  CUtensorMap mK = map3(d_in[6], 64, 1, CU_TENSOR_MAP_SWIZZLE_NONE, PR_K);
  CUtensorMap mV = map3(d_in[7], 64, 1, CU_TENSOR_MAP_SWIZZLE_NONE, PR_K);
  CUtensorMap mQ = map3(d_in[5], 64, 1, CU_TENSOR_MAP_SWIZZLE_64B, 2);
  CUtensorMap mO = map3(d_out, 64, 1, CU_TENSOR_MAP_SWIZZLE_64B, 2, 2);
  CUtensorMap mCr = make_map(enc, d_in[1], 2048, 2048, 64, 128, CU_TENSOR_MAP_SWIZZLE_128B, (CUtensorMapL2promotion)PR_C);
  CUtensorMap mCi = make_map(enc, d_in[2], 2048, 2048, 64, 128, CU_TENSOR_MAP_SWIZZLE_128B, (CUtensorMapL2promotion)PR_C);
  CUtensorMap mHr = make_map(enc, d_in[3], 640, 640, 64, 80, CU_TENSOR_MAP_SWIZZLE_128B);
  CUtensorMap mHi = make_map(enc, d_in[4], 640, 640, 64, 80, CU_TENSOR_MAP_SWIZZLE_128B);
  CUtensorMap mT = make_map(enc, gt, 2048, 1280, 64, 32, CU_TENSOR_MAP_SWIZZLE_128B);
  CUtensorMap mOut = make_map(enc, d_out, 1280, 2048, 80, 16, CU_TENSOR_MAP_SWIZZLE_NONE);
  Params p;
  p.hr = (const __nv_bfloat16*)d_in[3];
  p.hi = (const __nv_bfloat16*)d_in[4];
  p.q = (const __nv_bfloat16*)d_in[5];
  p.shift_k = (const __nv_bfloat16*)d_in[8];
  p.ssm_k = (const __nv_bfloat16*)d_in[9];
  p.ssm_D = (const __nv_bfloat16*)d_in[10];
  fused_kernel<<<NCTA, NTHREADS, SMEM_BYTES>>>(p, mX, mHr, mHi, mCr, mCi, mT, mKh, mK, mV, mOut, mQ, mO);
}
```

```cpp
#include <cuda_runtime.h>
#include <cuda.h>
#include <cuda_bf16.h>
#include <stdint.h>

#define STAGES 5
#define G_KV 5
#define G_T 20
#define XOWN 1
#define WPUB 2
#define NBE 7
#define CPRI 3
#define G_Q 30
#define G_H 25
#define DI 3
#define ZF32 0
#define FAHEAD 1
#define F01 1
#define JB 6
#define J0W 0
#define J1W 0
#define ORD 0
#define ALLF 1
#define EF 0
#define EFP 1
#define RFIRST 0
#define R_CONV 200
#define R_GEMM 112
#define R_AUX 88
#define NCTA 128
#define A_BYTES 16384
#define B_BYTES 20480
#define STAGE_BYTES 36864
#define NTHREADS 512

#define OFF_PART   (STAGES * STAGE_BYTES)
#define U_BYTES    4352
#define OFF_HT     (OFF_PART + 16384)
#define HC_BYTES   4128
#define HT_BYTES   8256
#define OFF_UB     (OFF_PART + 33024)
#define OFF_BAR    (OFF_PART + 46080)
#define SMEM_BYTES (OFF_BAR + 768 + 512)
__device__ __forceinline__ uint32_t ks_off(int i) { return OFF_PART + min(i, 2) * 8192; }
__device__ __forceinline__ uint32_t tap_off(int i) { return i < 3 ? OFF_UB + U_BYTES + i * 512 : OFF_BAR + 768; }
__device__ __forceinline__ uint32_t u_off(int c) { return (c == 0 || c == 3) ? OFF_UB + 2 * U_BYTES : (c == 2 ? OFF_UB + U_BYTES : OFF_UB); }
__device__ __forceinline__ uint32_t q_off(int i) { return i == 2 ? OFF_UB + U_BYTES : OFF_HT + i * 4096 - (i > 2 ? 3584 : 0); }

__device__ __align__(1024) unsigned char g_u[16 * 2 * 10 * A_BYTES];
__device__ __align__(1024) unsigned char g_t[1280 * 4096];
__device__ __align__(128) unsigned g_flag[32 * 32];
__device__ __align__(128) unsigned g_cnt[20 * 32];
__device__ unsigned g_ticket;
#define STAMP(i) do {} while (0)
#define ITC(i) do {} while (0)
#define STAMPC(i) do {} while (0)
#define CS(i) do {} while (0)
#define VAL(i, v) do {} while (0)

template<int N> __device__ __forceinline__ void wgmma_ss(float* d, uint64_t a, uint64_t b, int s);
template<int N> __device__ __forceinline__ void wgmma_rs(float* d, uint32_t a0, uint32_t a1, uint32_t a2, uint32_t a3, uint32_t b, int off, int s);
template<> __device__ __forceinline__ void wgmma_ss<160>(float* d, uint64_t descA, uint64_t descB, int scaleD) {
  asm volatile("{\n.reg .pred p;\nsetp.ne.b32 p, %82, 0;\n"
    "wgmma.mma_async.sync.aligned.m64n160k16.f32.bf16.bf16 {%0,%1,%2,%3,%4,%5,%6,%7,%8,%9,%10,%11,%12,%13,%14,%15,%16,%17,%18,%19,%20,%21,%22,%23,%24,%25,%26,%27,%28,%29,%30,%31,%32,%33,%34,%35,%36,%37,%38,%39,%40,%41,%42,%43,%44,%45,%46,%47,%48,%49,%50,%51,%52,%53,%54,%55,%56,%57,%58,%59,%60,%61,%62,%63,%64,%65,%66,%67,%68,%69,%70,%71,%72,%73,%74,%75,%76,%77,%78,%79}, %80, %81, p, 1, 1, 0, 0;\n}\n"
    : "+f"(d[0]),"+f"(d[1]),"+f"(d[2]),"+f"(d[3]),"+f"(d[4]),"+f"(d[5]),"+f"(d[6]),"+f"(d[7]),"+f"(d[8]),"+f"(d[9]),"+f"(d[10]),"+f"(d[11]),"+f"(d[12]),"+f"(d[13]),"+f"(d[14]),"+f"(d[15]),"+f"(d[16]),"+f"(d[17]),"+f"(d[18]),"+f"(d[19]),"+f"(d[20]),"+f"(d[21]),"+f"(d[22]),"+f"(d[23]),"+f"(d[24]),"+f"(d[25]),"+f"(d[26]),"+f"(d[27]),"+f"(d[28]),"+f"(d[29]),"+f"(d[30]),"+f"(d[31]),"+f"(d[32]),"+f"(d[33]),"+f"(d[34]),"+f"(d[35]),"+f"(d[36]),"+f"(d[37]),"+f"(d[38]),"+f"(d[39]),"+f"(d[40]),"+f"(d[41]),"+f"(d[42]),"+f"(d[43]),"+f"(d[44]),"+f"(d[45]),"+f"(d[46]),"+f"(d[47]),"+f"(d[48]),"+f"(d[49]),"+f"(d[50]),"+f"(d[51]),"+f"(d[52]),"+f"(d[53]),"+f"(d[54]),"+f"(d[55]),"+f"(d[56]),"+f"(d[57]),"+f"(d[58]),"+f"(d[59]),"+f"(d[60]),"+f"(d[61]),"+f"(d[62]),"+f"(d[63]),"+f"(d[64]),"+f"(d[65]),"+f"(d[66]),"+f"(d[67]),"+f"(d[68]),"+f"(d[69]),"+f"(d[70]),"+f"(d[71]),"+f"(d[72]),"+f"(d[73]),"+f"(d[74]),"+f"(d[75]),"+f"(d[76]),"+f"(d[77]),"+f"(d[78]),"+f"(d[79])
    : "l"(descA),"l"(descB),"r"(scaleD));
}
__device__ __forceinline__ void wgmma_ss_tb160(float* d, uint64_t descA, uint64_t descB, int scaleD) {
  asm volatile("{\n.reg .pred p;\nsetp.ne.b32 p, %82, 0;\n"
    "wgmma.mma_async.sync.aligned.m64n160k16.f32.bf16.bf16 {%0,%1,%2,%3,%4,%5,%6,%7,%8,%9,%10,%11,%12,%13,%14,%15,%16,%17,%18,%19,%20,%21,%22,%23,%24,%25,%26,%27,%28,%29,%30,%31,%32,%33,%34,%35,%36,%37,%38,%39,%40,%41,%42,%43,%44,%45,%46,%47,%48,%49,%50,%51,%52,%53,%54,%55,%56,%57,%58,%59,%60,%61,%62,%63,%64,%65,%66,%67,%68,%69,%70,%71,%72,%73,%74,%75,%76,%77,%78,%79}, %80, %81, p, 1, 1, 0, 1;\n}\n"
    : "+f"(d[0]),"+f"(d[1]),"+f"(d[2]),"+f"(d[3]),"+f"(d[4]),"+f"(d[5]),"+f"(d[6]),"+f"(d[7]),"+f"(d[8]),"+f"(d[9]),"+f"(d[10]),"+f"(d[11]),"+f"(d[12]),"+f"(d[13]),"+f"(d[14]),"+f"(d[15]),"+f"(d[16]),"+f"(d[17]),"+f"(d[18]),"+f"(d[19]),"+f"(d[20]),"+f"(d[21]),"+f"(d[22]),"+f"(d[23]),"+f"(d[24]),"+f"(d[25]),"+f"(d[26]),"+f"(d[27]),"+f"(d[28]),"+f"(d[29]),"+f"(d[30]),"+f"(d[31]),"+f"(d[32]),"+f"(d[33]),"+f"(d[34]),"+f"(d[35]),"+f"(d[36]),"+f"(d[37]),"+f"(d[38]),"+f"(d[39]),"+f"(d[40]),"+f"(d[41]),"+f"(d[42]),"+f"(d[43]),"+f"(d[44]),"+f"(d[45]),"+f"(d[46]),"+f"(d[47]),"+f"(d[48]),"+f"(d[49]),"+f"(d[50]),"+f"(d[51]),"+f"(d[52]),"+f"(d[53]),"+f"(d[54]),"+f"(d[55]),"+f"(d[56]),"+f"(d[57]),"+f"(d[58]),"+f"(d[59]),"+f"(d[60]),"+f"(d[61]),"+f"(d[62]),"+f"(d[63]),"+f"(d[64]),"+f"(d[65]),"+f"(d[66]),"+f"(d[67]),"+f"(d[68]),"+f"(d[69]),"+f"(d[70]),"+f"(d[71]),"+f"(d[72]),"+f"(d[73]),"+f"(d[74]),"+f"(d[75]),"+f"(d[76]),"+f"(d[77]),"+f"(d[78]),"+f"(d[79])
    : "l"(descA),"l"(descB),"r"(scaleD));
}
template<> __device__ __forceinline__ void wgmma_ss<80>(float* d, uint64_t descA, uint64_t descB, int scaleD) {
  asm volatile("{\n.reg .pred p;\nsetp.ne.b32 p, %42, 0;\n"
    "wgmma.mma_async.sync.aligned.m64n80k16.f32.bf16.bf16 {%0,%1,%2,%3,%4,%5,%6,%7,%8,%9,%10,%11,%12,%13,%14,%15,%16,%17,%18,%19,%20,%21,%22,%23,%24,%25,%26,%27,%28,%29,%30,%31,%32,%33,%34,%35,%36,%37,%38,%39}, %40, %41, p, 1, 1, 0, 0;\n}\n"
    : "+f"(d[0]),"+f"(d[1]),"+f"(d[2]),"+f"(d[3]),"+f"(d[4]),"+f"(d[5]),"+f"(d[6]),"+f"(d[7]),"+f"(d[8]),"+f"(d[9]),"+f"(d[10]),"+f"(d[11]),"+f"(d[12]),"+f"(d[13]),"+f"(d[14]),"+f"(d[15]),"+f"(d[16]),"+f"(d[17]),"+f"(d[18]),"+f"(d[19]),"+f"(d[20]),"+f"(d[21]),"+f"(d[22]),"+f"(d[23]),"+f"(d[24]),"+f"(d[25]),"+f"(d[26]),"+f"(d[27]),"+f"(d[28]),"+f"(d[29]),"+f"(d[30]),"+f"(d[31]),"+f"(d[32]),"+f"(d[33]),"+f"(d[34]),"+f"(d[35]),"+f"(d[36]),"+f"(d[37]),"+f"(d[38]),"+f"(d[39])
    : "l"(descA),"l"(descB),"r"(scaleD));
}
template<> __device__ __forceinline__ void wgmma_rs<16>(float* d, uint32_t a0, uint32_t a1, uint32_t a2, uint32_t a3, uint32_t descLo, int off, int scaleD) {
  asm volatile("{\n.reg .pred p;\n.reg .b32 t;\n.reg .b64 d;\nsetp.ne.b32 p, %14, 0;\nadd.u32 t, %12, %13;\nmov.b64 d, {t, 0xC0000010};\n"
    "wgmma.mma_async.sync.aligned.m64n16k16.f32.bf16.bf16 {%0,%1,%2,%3,%4,%5,%6,%7}, {%8,%9,%10,%11}, d, p, 1, 1, 0;\n}\n"
    : "+f"(d[0]),"+f"(d[1]),"+f"(d[2]),"+f"(d[3]),"+f"(d[4]),"+f"(d[5]),"+f"(d[6]),"+f"(d[7])
    : "r"(a0),"r"(a1),"r"(a2),"r"(a3),"r"(descLo),"r"(off),"r"(scaleD));
}
template<> __device__ __forceinline__ void wgmma_rs<32>(float* d, uint32_t a0, uint32_t a1, uint32_t a2, uint32_t a3, uint32_t descLo, int off, int scaleD) {
  asm volatile("{\n.reg .pred p;\n.reg .b32 t;\n.reg .b64 d;\nsetp.ne.b32 p, %22, 0;\nadd.u32 t, %20, %21;\nmov.b64 d, {t, 0xC0000010};\n"
    "wgmma.mma_async.sync.aligned.m64n32k16.f32.bf16.bf16 {%0,%1,%2,%3,%4,%5,%6,%7,%8,%9,%10,%11,%12,%13,%14,%15}, {%16,%17,%18,%19}, d, p, 1, 1, 0;\n}\n"
    : "+f"(d[0]),"+f"(d[1]),"+f"(d[2]),"+f"(d[3]),"+f"(d[4]),"+f"(d[5]),"+f"(d[6]),"+f"(d[7]),"+f"(d[8]),"+f"(d[9]),"+f"(d[10]),"+f"(d[11]),"+f"(d[12]),"+f"(d[13]),"+f"(d[14]),"+f"(d[15])
    : "r"(a0),"r"(a1),"r"(a2),"r"(a3),"r"(descLo),"r"(off),"r"(scaleD));
}
template<> __device__ __forceinline__ void wgmma_rs<48>(float* d, uint32_t a0, uint32_t a1, uint32_t a2, uint32_t a3, uint32_t descLo, int off, int scaleD) {
  asm volatile("{\n.reg .pred p;\n.reg .b32 t;\n.reg .b64 d;\nsetp.ne.b32 p, %30, 0;\nadd.u32 t, %28, %29;\nmov.b64 d, {t, 0xC0000010};\n"
    "wgmma.mma_async.sync.aligned.m64n48k16.f32.bf16.bf16 {%0,%1,%2,%3,%4,%5,%6,%7,%8,%9,%10,%11,%12,%13,%14,%15,%16,%17,%18,%19,%20,%21,%22,%23}, {%24,%25,%26,%27}, d, p, 1, 1, 0;\n}\n"
    : "+f"(d[0]),"+f"(d[1]),"+f"(d[2]),"+f"(d[3]),"+f"(d[4]),"+f"(d[5]),"+f"(d[6]),"+f"(d[7]),"+f"(d[8]),"+f"(d[9]),"+f"(d[10]),"+f"(d[11]),"+f"(d[12]),"+f"(d[13]),"+f"(d[14]),"+f"(d[15]),"+f"(d[16]),"+f"(d[17]),"+f"(d[18]),"+f"(d[19]),"+f"(d[20]),"+f"(d[21]),"+f"(d[22]),"+f"(d[23])
    : "r"(a0),"r"(a1),"r"(a2),"r"(a3),"r"(descLo),"r"(off),"r"(scaleD));
}
template<> __device__ __forceinline__ void wgmma_rs<64>(float* d, uint32_t a0, uint32_t a1, uint32_t a2, uint32_t a3, uint32_t descLo, int off, int scaleD) {
  asm volatile("{\n.reg .pred p;\n.reg .b32 t;\n.reg .b64 d;\nsetp.ne.b32 p, %38, 0;\nadd.u32 t, %36, %37;\nmov.b64 d, {t, 0xC0000010};\n"
    "wgmma.mma_async.sync.aligned.m64n64k16.f32.bf16.bf16 {%0,%1,%2,%3,%4,%5,%6,%7,%8,%9,%10,%11,%12,%13,%14,%15,%16,%17,%18,%19,%20,%21,%22,%23,%24,%25,%26,%27,%28,%29,%30,%31}, {%32,%33,%34,%35}, d, p, 1, 1, 0;\n}\n"
    : "+f"(d[0]),"+f"(d[1]),"+f"(d[2]),"+f"(d[3]),"+f"(d[4]),"+f"(d[5]),"+f"(d[6]),"+f"(d[7]),"+f"(d[8]),"+f"(d[9]),"+f"(d[10]),"+f"(d[11]),"+f"(d[12]),"+f"(d[13]),"+f"(d[14]),"+f"(d[15]),"+f"(d[16]),"+f"(d[17]),"+f"(d[18]),"+f"(d[19]),"+f"(d[20]),"+f"(d[21]),"+f"(d[22]),"+f"(d[23]),"+f"(d[24]),"+f"(d[25]),"+f"(d[26]),"+f"(d[27]),"+f"(d[28]),"+f"(d[29]),"+f"(d[30]),"+f"(d[31])
    : "r"(a0),"r"(a1),"r"(a2),"r"(a3),"r"(descLo),"r"(off),"r"(scaleD));
}
template<> __device__ __forceinline__ void wgmma_rs<80>(float* d, uint32_t a0, uint32_t a1, uint32_t a2, uint32_t a3, uint32_t descLo, int off, int scaleD) {
  asm volatile("{\n.reg .pred p;\n.reg .b32 t;\n.reg .b64 d;\nsetp.ne.b32 p, %46, 0;\nadd.u32 t, %44, %45;\nmov.b64 d, {t, 0xC0000010};\n"
    "wgmma.mma_async.sync.aligned.m64n80k16.f32.bf16.bf16 {%0,%1,%2,%3,%4,%5,%6,%7,%8,%9,%10,%11,%12,%13,%14,%15,%16,%17,%18,%19,%20,%21,%22,%23,%24,%25,%26,%27,%28,%29,%30,%31,%32,%33,%34,%35,%36,%37,%38,%39}, {%40,%41,%42,%43}, d, p, 1, 1, 0;\n}\n"
    : "+f"(d[0]),"+f"(d[1]),"+f"(d[2]),"+f"(d[3]),"+f"(d[4]),"+f"(d[5]),"+f"(d[6]),"+f"(d[7]),"+f"(d[8]),"+f"(d[9]),"+f"(d[10]),"+f"(d[11]),"+f"(d[12]),"+f"(d[13]),"+f"(d[14]),"+f"(d[15]),"+f"(d[16]),"+f"(d[17]),"+f"(d[18]),"+f"(d[19]),"+f"(d[20]),"+f"(d[21]),"+f"(d[22]),"+f"(d[23]),"+f"(d[24]),"+f"(d[25]),"+f"(d[26]),"+f"(d[27]),"+f"(d[28]),"+f"(d[29]),"+f"(d[30]),"+f"(d[31]),"+f"(d[32]),"+f"(d[33]),"+f"(d[34]),"+f"(d[35]),"+f"(d[36]),"+f"(d[37]),"+f"(d[38]),"+f"(d[39])
    : "r"(a0),"r"(a1),"r"(a2),"r"(a3),"r"(descLo),"r"(off),"r"(scaleD));
}
template<> __device__ __forceinline__ void wgmma_rs<96>(float* d, uint32_t a0, uint32_t a1, uint32_t a2, uint32_t a3, uint32_t descLo, int off, int scaleD) {
  asm volatile("{\n.reg .pred p;\n.reg .b32 t;\n.reg .b64 d;\nsetp.ne.b32 p, %54, 0;\nadd.u32 t, %52, %53;\nmov.b64 d, {t, 0xC0000010};\n"
    "wgmma.mma_async.sync.aligned.m64n96k16.f32.bf16.bf16 {%0,%1,%2,%3,%4,%5,%6,%7,%8,%9,%10,%11,%12,%13,%14,%15,%16,%17,%18,%19,%20,%21,%22,%23,%24,%25,%26,%27,%28,%29,%30,%31,%32,%33,%34,%35,%36,%37,%38,%39,%40,%41,%42,%43,%44,%45,%46,%47}, {%48,%49,%50,%51}, d, p, 1, 1, 0;\n}\n"
    : "+f"(d[0]),"+f"(d[1]),"+f"(d[2]),"+f"(d[3]),"+f"(d[4]),"+f"(d[5]),"+f"(d[6]),"+f"(d[7]),"+f"(d[8]),"+f"(d[9]),"+f"(d[10]),"+f"(d[11]),"+f"(d[12]),"+f"(d[13]),"+f"(d[14]),"+f"(d[15]),"+f"(d[16]),"+f"(d[17]),"+f"(d[18]),"+f"(d[19]),"+f"(d[20]),"+f"(d[21]),"+f"(d[22]),"+f"(d[23]),"+f"(d[24]),"+f"(d[25]),"+f"(d[26]),"+f"(d[27]),"+f"(d[28]),"+f"(d[29]),"+f"(d[30]),"+f"(d[31]),"+f"(d[32]),"+f"(d[33]),"+f"(d[34]),"+f"(d[35]),"+f"(d[36]),"+f"(d[37]),"+f"(d[38]),"+f"(d[39]),"+f"(d[40]),"+f"(d[41]),"+f"(d[42]),"+f"(d[43]),"+f"(d[44]),"+f"(d[45]),"+f"(d[46]),"+f"(d[47])
    : "r"(a0),"r"(a1),"r"(a2),"r"(a3),"r"(descLo),"r"(off),"r"(scaleD));
}
template<> __device__ __forceinline__ void wgmma_rs<112>(float* d, uint32_t a0, uint32_t a1, uint32_t a2, uint32_t a3, uint32_t descLo, int off, int scaleD) {
  asm volatile("{\n.reg .pred p;\n.reg .b32 t;\n.reg .b64 d;\nsetp.ne.b32 p, %62, 0;\nadd.u32 t, %60, %61;\nmov.b64 d, {t, 0xC0000010};\n"
    "wgmma.mma_async.sync.aligned.m64n112k16.f32.bf16.bf16 {%0,%1,%2,%3,%4,%5,%6,%7,%8,%9,%10,%11,%12,%13,%14,%15,%16,%17,%18,%19,%20,%21,%22,%23,%24,%25,%26,%27,%28,%29,%30,%31,%32,%33,%34,%35,%36,%37,%38,%39,%40,%41,%42,%43,%44,%45,%46,%47,%48,%49,%50,%51,%52,%53,%54,%55}, {%56,%57,%58,%59}, d, p, 1, 1, 0;\n}\n"
    : "+f"(d[0]),"+f"(d[1]),"+f"(d[2]),"+f"(d[3]),"+f"(d[4]),"+f"(d[5]),"+f"(d[6]),"+f"(d[7]),"+f"(d[8]),"+f"(d[9]),"+f"(d[10]),"+f"(d[11]),"+f"(d[12]),"+f"(d[13]),"+f"(d[14]),"+f"(d[15]),"+f"(d[16]),"+f"(d[17]),"+f"(d[18]),"+f"(d[19]),"+f"(d[20]),"+f"(d[21]),"+f"(d[22]),"+f"(d[23]),"+f"(d[24]),"+f"(d[25]),"+f"(d[26]),"+f"(d[27]),"+f"(d[28]),"+f"(d[29]),"+f"(d[30]),"+f"(d[31]),"+f"(d[32]),"+f"(d[33]),"+f"(d[34]),"+f"(d[35]),"+f"(d[36]),"+f"(d[37]),"+f"(d[38]),"+f"(d[39]),"+f"(d[40]),"+f"(d[41]),"+f"(d[42]),"+f"(d[43]),"+f"(d[44]),"+f"(d[45]),"+f"(d[46]),"+f"(d[47]),"+f"(d[48]),"+f"(d[49]),"+f"(d[50]),"+f"(d[51]),"+f"(d[52]),"+f"(d[53]),"+f"(d[54]),"+f"(d[55])
    : "r"(a0),"r"(a1),"r"(a2),"r"(a3),"r"(descLo),"r"(off),"r"(scaleD));
}
template<> __device__ __forceinline__ void wgmma_rs<128>(float* d, uint32_t a0, uint32_t a1, uint32_t a2, uint32_t a3, uint32_t descLo, int off, int scaleD) {
  asm volatile("{\n.reg .pred p;\n.reg .b32 t;\n.reg .b64 d;\nsetp.ne.b32 p, %70, 0;\nadd.u32 t, %68, %69;\nmov.b64 d, {t, 0xC0000010};\n"
    "wgmma.mma_async.sync.aligned.m64n128k16.f32.bf16.bf16 {%0,%1,%2,%3,%4,%5,%6,%7,%8,%9,%10,%11,%12,%13,%14,%15,%16,%17,%18,%19,%20,%21,%22,%23,%24,%25,%26,%27,%28,%29,%30,%31,%32,%33,%34,%35,%36,%37,%38,%39,%40,%41,%42,%43,%44,%45,%46,%47,%48,%49,%50,%51,%52,%53,%54,%55,%56,%57,%58,%59,%60,%61,%62,%63}, {%64,%65,%66,%67}, d, p, 1, 1, 0;\n}\n"
    : "+f"(d[0]),"+f"(d[1]),"+f"(d[2]),"+f"(d[3]),"+f"(d[4]),"+f"(d[5]),"+f"(d[6]),"+f"(d[7]),"+f"(d[8]),"+f"(d[9]),"+f"(d[10]),"+f"(d[11]),"+f"(d[12]),"+f"(d[13]),"+f"(d[14]),"+f"(d[15]),"+f"(d[16]),"+f"(d[17]),"+f"(d[18]),"+f"(d[19]),"+f"(d[20]),"+f"(d[21]),"+f"(d[22]),"+f"(d[23]),"+f"(d[24]),"+f"(d[25]),"+f"(d[26]),"+f"(d[27]),"+f"(d[28]),"+f"(d[29]),"+f"(d[30]),"+f"(d[31]),"+f"(d[32]),"+f"(d[33]),"+f"(d[34]),"+f"(d[35]),"+f"(d[36]),"+f"(d[37]),"+f"(d[38]),"+f"(d[39]),"+f"(d[40]),"+f"(d[41]),"+f"(d[42]),"+f"(d[43]),"+f"(d[44]),"+f"(d[45]),"+f"(d[46]),"+f"(d[47]),"+f"(d[48]),"+f"(d[49]),"+f"(d[50]),"+f"(d[51]),"+f"(d[52]),"+f"(d[53]),"+f"(d[54]),"+f"(d[55]),"+f"(d[56]),"+f"(d[57]),"+f"(d[58]),"+f"(d[59]),"+f"(d[60]),"+f"(d[61]),"+f"(d[62]),"+f"(d[63])
    : "r"(a0),"r"(a1),"r"(a2),"r"(a3),"r"(descLo),"r"(off),"r"(scaleD));
}

__device__ __forceinline__ uint32_t smem_u32(const void* p) { return (uint32_t)__cvta_generic_to_shared(p); }
__device__ __forceinline__ uint64_t mkdesc(uint32_t addr, uint32_t lbo, uint32_t sbo, int swz) {
  return (uint64_t)((addr & 0x3FFFF) >> 4) | ((uint64_t)(lbo >> 4) << 16) | ((uint64_t)(sbo >> 4) << 32) | ((uint64_t)swz << 62);
}
__device__ __forceinline__ unsigned long long gtime() { unsigned long long t; asm volatile("mov.u64 %0, %%globaltimer;" : "=l"(t)); return t; }
__device__ __forceinline__ void mbar_init(uint32_t bar, int count) { asm volatile("mbarrier.init.shared::cta.b64 [%0], %1;" ::"r"(bar), "r"(count) : "memory"); }
__device__ __forceinline__ void mbar_expect_tx(uint32_t bar, uint32_t bytes) { asm volatile("mbarrier.arrive.expect_tx.shared::cta.b64 _, [%0], %1;" ::"r"(bar), "r"(bytes) : "memory"); }
__device__ __forceinline__ void mbar_arrive(uint32_t bar) { asm volatile("mbarrier.arrive.shared::cta.b64 _, [%0];" ::"r"(bar) : "memory"); }
__device__ __forceinline__ void mbar_arrive_cta(uint32_t bar, uint32_t cta) {
  asm volatile("{\n.reg .b32 ra;\nmapa.shared::cluster.u32 ra, %0, %1;\nmbarrier.arrive.shared::cluster.b64 _, [ra];\n}\n" ::"r"(bar), "r"(cta) : "memory");
}
__device__ __forceinline__ void mbar_wait(uint32_t bar, uint32_t parity) {
  uint32_t ok;
  int tries = 0;
#pragma unroll 1
  do {
    asm volatile("{\n.reg .pred p;\nmbarrier.try_wait.parity.shared::cta.b64 p, [%1], %2;\nselp.u32 %0, 1, 0, p;\n}\n" : "=r"(ok) : "r"(bar), "r"(parity) : "memory");
  } while (!ok && ++tries < (1 << 17));
}
#define SLP 100
__device__ __forceinline__ void mbar_wait_slow(uint32_t bar, uint32_t parity) {
  uint32_t ok;
  int tries = 0;
#pragma unroll 1
  do {
    asm volatile("{\n.reg .pred p;\nmbarrier.test_wait.parity.shared::cta.b64 p, [%1], %2;\nselp.u32 %0, 1, 0, p;\n}\n" : "=r"(ok) : "r"(bar), "r"(parity) : "memory");
    if (!ok) __nanosleep(SLP);
  } while (!ok && ++tries < (1 << 17));
}
__device__ __forceinline__ uint32_t mbar_test(uint32_t bar, uint32_t parity) {
  uint32_t ok;
  asm volatile("{\n.reg .pred p;\nmbarrier.test_wait.parity.shared::cta.b64 p, [%1], %2;\nselp.u32 %0, 1, 0, p;\n}\n" : "=r"(ok) : "r"(bar), "r"(parity) : "memory");
  return ok;
}
__device__ __forceinline__ void tma_load_2d(uint32_t dst, const CUtensorMap* map, int c0, int c1, uint32_t bar) {
  asm volatile("cp.async.bulk.tensor.2d.shared::cluster.global.mbarrier::complete_tx::bytes [%0], [%1, {%3, %4}], [%2];"
               ::"r"(dst), "l"((uint64_t)map), "r"(bar), "r"(c0), "r"(c1) : "memory");
}
__device__ __forceinline__ void tma_load_2d_mc(uint32_t dst, const CUtensorMap* map, int c0, int c1, uint32_t bar, uint16_t mask) {
  asm volatile("cp.async.bulk.tensor.2d.shared::cluster.global.mbarrier::complete_tx::bytes.multicast::cluster [%0], [%1, {%3, %4}], [%2], %5;"
               ::"r"(dst), "l"((uint64_t)map), "r"(bar), "r"(c0), "r"(c1), "h"(mask) : "memory");
}
__device__ __forceinline__ void tma_prefetch_2d(const CUtensorMap* map, int c0, int c1) {
  asm volatile("cp.async.bulk.prefetch.tensor.2d.L2.global [%0, {%1, %2}];" ::"l"((uint64_t)map), "r"(c0), "r"(c1) : "memory");
}
__device__ __forceinline__ void bulk_load(uint32_t dst, const void* src, uint32_t bytes, uint32_t bar) {
  asm volatile("cp.async.bulk.shared::cluster.global.mbarrier::complete_tx::bytes [%0], [%1], %2, [%3];"
               ::"r"(dst), "l"((uint64_t)src), "r"(bytes), "r"(bar) : "memory");
}
__device__ __forceinline__ void bulk_store(void* dst, uint32_t src, uint32_t bytes) {
  asm volatile("cp.async.bulk.global.shared::cta.bulk_group [%0], [%1], %2;" ::"l"((uint64_t)dst), "r"(src), "r"(bytes) : "memory");
}
__device__ __forceinline__ void bulk_prefetch(const void* src, uint32_t bytes) {
  asm volatile("cp.async.bulk.prefetch.L2.global [%0], %1;" ::"l"((uint64_t)src), "r"(bytes) : "memory");
}
__device__ __forceinline__ void tma_reduce_add_2d(const CUtensorMap* map, int c0, int c1, uint32_t src) {
  asm volatile("cp.reduce.async.bulk.tensor.2d.global.shared::cta.add.tile.bulk_group [%0, {%1, %2}], [%3];"
               ::"l"((uint64_t)map), "r"(c0), "r"(c1), "r"(src) : "memory");
}
__device__ __forceinline__ void bulk_commit() { asm volatile("cp.async.bulk.commit_group;" ::: "memory"); }
__device__ __forceinline__ void bulk_wait_all() { asm volatile("cp.async.bulk.wait_group 0;" ::: "memory"); }
__device__ __forceinline__ void bulk_wait_read() { asm volatile("cp.async.bulk.wait_group.read 0;" ::: "memory"); }
__device__ __forceinline__ void fence_async_smem() { asm volatile("fence.proxy.async.shared::cta;" ::: "memory"); }
__device__ __forceinline__ void fence_async_all() { asm volatile("fence.proxy.async.global;" ::: "memory"); }
__device__ __forceinline__ void cluster_arrive() { asm volatile("barrier.cluster.arrive.relaxed.aligned;" ::: "memory"); }
__device__ __forceinline__ void cluster_wait() { asm volatile("barrier.cluster.wait.aligned;" ::: "memory"); }
__device__ __forceinline__ void prefetch_map(const CUtensorMap* m) { asm volatile("prefetch.tensormap [%0];" ::"l"((uint64_t)m) : "memory"); }
__device__ __forceinline__ uint32_t cluster_rank() { uint32_t r; asm volatile("mov.u32 %0, %%cluster_ctarank;" : "=r"(r)); return r; }
__device__ __forceinline__ uint32_t smid() { uint32_t r; asm volatile("mov.u32 %0, %%smid;" : "=r"(r)); return r; }
__device__ __forceinline__ bool elect_one() {
  uint32_t p;
  asm volatile("{\n.reg .pred P;\nelect.sync _|P, 0xffffffff;\nselp.b32 %0, 1, 0, P;\n}\n" : "=r"(p));
  return p != 0;
}
__device__ __forceinline__ void wg_fence() { asm volatile("wgmma.fence.sync.aligned;" ::: "memory"); }
__device__ __forceinline__ void wg_commit() { asm volatile("wgmma.commit_group.sync.aligned;" ::: "memory"); }
template <int N> __device__ __forceinline__ void wg_wait() { asm volatile("wgmma.wait_group.sync.aligned %0;" ::"n"(N) : "memory"); }
template <int ID, int N> __device__ __forceinline__ void bar_sync() { asm volatile("bar.sync %0, %1;" ::"n"(ID), "n"(N) : "memory"); }
template <int ID, int N> __device__ __forceinline__ void bar_arrive() { asm volatile("bar.arrive %0, %1;" ::"n"(ID), "n"(N) : "memory"); }
template <int R> __device__ __forceinline__ void reg_inc() { asm volatile("setmaxnreg.inc.sync.aligned.u32 %0;" ::"n"(R)); }
template <int R> __device__ __forceinline__ void reg_dec() { asm volatile("setmaxnreg.dec.sync.aligned.u32 %0;" ::"n"(R)); }
__device__ __forceinline__ unsigned ld_acquire(const unsigned* p) { unsigned v; asm volatile("ld.acquire.gpu.global.u32 %0, [%1];" : "=r"(v) : "l"(p) : "memory"); return v; }
__device__ __forceinline__ void st_release(unsigned* p, unsigned v) { asm volatile("st.release.gpu.global.u32 [%0], %1;" ::"l"(p), "r"(v) : "memory"); }
__device__ __forceinline__ void red_release_add(unsigned* p, unsigned v) { asm volatile("red.release.gpu.global.add.u32 [%0], %1;" ::"l"(p), "r"(v) : "memory"); }
__device__ __forceinline__ uint4 ld_poll(const unsigned* p) {
  uint4 f;
  asm volatile("ld.acquire.gpu.global.v4.u32 {%0,%1,%2,%3}, [%4];" : "=r"(f.x), "=r"(f.y), "=r"(f.z), "=r"(f.w) : "l"(p) : "memory");
  return f;
}
__device__ __forceinline__ void wait_ge(const unsigned* p, unsigned target) {
  int tries = 0;
#pragma unroll 1
  while ((int)(ld_acquire(p) - target) < 0) {
    __nanosleep(40);
    if (++tries > (1 << 18)) break;
  }
}
__device__ __forceinline__ uint32_t lds32(uint32_t a) { uint32_t v; asm volatile("ld.shared.u32 %0, [%1];" : "=r"(v) : "r"(a) : "memory"); return v; }
__device__ __forceinline__ uint4 lds128(uint32_t a) { uint4 v; asm volatile("ld.shared.v4.u32 {%0,%1,%2,%3}, [%4];" : "=r"(v.x), "=r"(v.y), "=r"(v.z), "=r"(v.w) : "r"(a) : "memory"); return v; }
__device__ __forceinline__ float4 lds128f(uint32_t a) { float4 v; asm volatile("ld.shared.v4.f32 {%0,%1,%2,%3}, [%4];" : "=f"(v.x), "=f"(v.y), "=f"(v.z), "=f"(v.w) : "r"(a) : "memory"); return v; }
__device__ __forceinline__ void sts32f(uint32_t a, float v) { asm volatile("st.shared.f32 [%0], %1;" ::"r"(a), "f"(v) : "memory"); }
__device__ __forceinline__ void sts128(uint32_t a, uint4 v) { asm volatile("st.shared.v4.u32 [%0], {%1,%2,%3,%4};" ::"r"(a), "r"(v.x), "r"(v.y), "r"(v.z), "r"(v.w) : "memory"); }
__device__ __forceinline__ void stmatrix_x4(uint32_t a, uint32_t r0, uint32_t r1, uint32_t r2, uint32_t r3) {
  asm volatile("stmatrix.sync.aligned.m8n8.x4.shared.b16 [%0], {%1,%2,%3,%4};" ::"r"(a), "r"(r0), "r"(r1), "r"(r2), "r"(r3) : "memory");
}
__device__ __forceinline__ void stmatrix_x4_trans(uint32_t a, uint32_t r0, uint32_t r1, uint32_t r2, uint32_t r3) {
  asm volatile("stmatrix.sync.aligned.m8n8.x4.trans.shared.b16 [%0], {%1,%2,%3,%4};" ::"r"(a), "r"(r0), "r"(r1), "r"(r2), "r"(r3) : "memory");
}
__device__ __forceinline__ uint32_t pack_bf16(float lo, float hi) {
  uint32_t r; asm("cvt.rn.bf16x2.f32 %0, %1, %2;" : "=r"(r) : "f"(hi), "f"(lo)); return r;
}
__device__ __forceinline__ uint32_t bmul2(uint32_t a, uint32_t b) { uint32_t r; asm("mul.rn.bf16x2 %0, %1, %2;" : "=r"(r) : "r"(a), "r"(b)); return r; }
__device__ __forceinline__ uint32_t badd2(uint32_t a, uint32_t b) { uint32_t r; asm("add.rn.bf16x2 %0, %1, %2;" : "=r"(r) : "r"(a), "r"(b)); return r; }
__device__ __forceinline__ uint32_t ldg32(const void* p) { uint32_t v; asm volatile("ld.global.nc.u32 %0, [%1];" : "=r"(v) : "l"(p)); return v; }

__device__ __forceinline__ void tma_load_3d_mc(uint32_t dst, const CUtensorMap* map, int c0, int c1, int c2, uint32_t bar, uint16_t mask) {
  asm volatile("cp.async.bulk.tensor.3d.shared::cluster.global.mbarrier::complete_tx::bytes.multicast::cluster [%0], [%1, {%3, %4, %5}], [%2], %6;"
               ::"r"(dst), "l"((uint64_t)map), "r"(bar), "r"(c0), "r"(c1), "r"(c2), "h"(mask) : "memory");
}
__device__ __forceinline__ void tma_load_3d(uint32_t dst, const CUtensorMap* map, int c0, int c1, int c2, uint32_t bar) {
  asm volatile("cp.async.bulk.tensor.3d.shared::cluster.global.mbarrier::complete_tx::bytes [%0], [%1, {%3, %4, %5}], [%2];"
               ::"r"(dst), "l"((uint64_t)map), "r"(bar), "r"(c0), "r"(c1), "r"(c2) : "memory");
}
__device__ __forceinline__ void tma_load_5d(uint32_t dst, const CUtensorMap* map, int c0, int c4, uint32_t bar) {
  asm volatile("cp.async.bulk.tensor.5d.shared::cluster.global.mbarrier::complete_tx::bytes [%0], [%1, {%3, %5, %5, %5, %4}], [%2];"
               ::"r"(dst), "l"((uint64_t)map), "r"(bar), "r"(c0), "r"(c4), "r"(0) : "memory");
}
__device__ __forceinline__ void tma_store_2d(const CUtensorMap* map, int c0, int c1, uint32_t src) {
  asm volatile("cp.async.bulk.tensor.2d.global.shared::cta.tile.bulk_group [%0, {%1, %2}], [%3];"
               ::"l"((uint64_t)map), "r"(c0), "r"(c1), "r"(src) : "memory");
}
__device__ __forceinline__ void red_relaxed_add(unsigned* p, unsigned v) { asm volatile("red.relaxed.gpu.global.add.u32 [%0], %1;" ::"l"(p), "r"(v) : "memory"); }
__device__ __forceinline__ uint32_t mapa(uint32_t a, uint32_t cta) { uint32_t r; asm("mapa.shared::cluster.u32 %0, %1, %2;" : "=r"(r) : "r"(a), "r"(cta)); return r; }
__device__ __forceinline__ void st_async128(uint32_t a, uint4 v, uint32_t bar) {
  asm volatile("st.async.weak.shared::cluster.mbarrier::complete_tx::bytes.v4.b32 [%0], {%1,%2,%3,%4}, [%5];"
               ::"r"(a), "r"(v.x), "r"(v.y), "r"(v.z), "r"(v.w), "r"(bar) : "memory");
}
__device__ __forceinline__ void st_relaxed(unsigned* p, unsigned v) { asm volatile("st.relaxed.gpu.global.u32 [%0], %1;" ::"l"(p), "r"(v) : "memory"); }
__device__ __forceinline__ uint4 ldg128(const void* p) {
  uint4 v; asm volatile("ld.global.nc.L1::no_allocate.v4.u32 {%0,%1,%2,%3}, [%4];" : "=r"(v.x), "=r"(v.y), "=r"(v.z), "=r"(v.w) : "l"(p)); return v;
}
__device__ __forceinline__ uint32_t lds16(uint32_t a) { uint16_t v; asm volatile("ld.shared.u16 %0, [%1];" : "=h"(v) : "r"(a) : "memory"); return v; }
__device__ __forceinline__ float bf_lo(uint32_t v) { return __uint_as_float(v << 16); }
__device__ __forceinline__ float bf_hi(uint32_t v) { return __uint_as_float(v & 0xffff0000u); }

#define BAR_FULL(s)  (bars + 8 * (s))
#define BAR_EMPTY(s) (bars + 8 * (5 + (s)))
#define BAR_KV(i)    (bars + 8 * (10 + (i)))
#define BAR_XFULL(g) (bars + 8 * (15 + (g)))
#define BAR_U(c)     (bars + 8 * (17 + (c)))
#define BAR_TAB(c)   (bars + 8 * (22 + (c)))
#define BAR_XFREE    (bars + 8 * 27)
#define BAR_EPOCH    (bars + 8 * 28)
#define BAR_CDONE    (bars + 8 * 29)
#define BAR_TH       (bars + 8 * 30)
#define EPOCH_WORD   (bars + 8 * 31)
#define NB_G0 2
#define NB_G1 3
#define NB_AUX 4
#define NB_PRE 5
#define NB_PUB 6
#define NB_T0 7
#define NB_PFULL 8
#define NB_PFREE 9

__device__ __forceinline__ void frag_load(uint32_t (&f)[16], uint32_t h0, int B) {
  const uint32_t hp = h0 + 512 * B;
  f[0] = lds32(hp);
#pragma unroll
  for (int j = 0; j < 4; j++) {
    f[4 * j + 1] = lds32(hp + 32 * j + 16);
    f[4 * j + 3] = lds32(hp + 32 * j + 32);
  }
}
template <int B>
__device__ __forceinline__ void conv_issue(float* acc, uint32_t (&f)[16], uint32_t desc, uint32_t h0) {
#pragma unroll
  for (int j = 0; j < 4; j++) {
    asm volatile("lop3.b32 %0, %1, %2, 0x80000000, 0xf8;" : "=r"(f[4 * j + 2]) : "r"(f[4 * j + 1]), "r"(h0) : "memory");
    if (j < 3) asm volatile("lop3.b32 %0, %1, %2, 0x80000000, 0xf8;" : "=r"(f[4 * j + 4]) : "r"(f[4 * j + 3]), "r"(h0) : "memory");
  }
  wg_fence();
#pragma unroll
  for (int j = 0; j < 4; j++) wgmma_rs<128 - 16 * B>(acc, f[4 * j], f[4 * j + 1], f[4 * j + 2], f[4 * j + 3], desc, 32 * B + 2 * j, B >= 2 || j != 0);
  wg_commit();
}
template <int B>
__device__ __forceinline__ void conv_batch(float* acc, uint32_t (&f)[16], uint32_t hp, uint32_t desc) {
  frag_load(f, hp, B);
  conv_issue<B>(acc, f, desc, hp);
}
template <int N>
__device__ __forceinline__ void conv_rename(float* acc) {
#pragma unroll
  for (int i = 0; i < N / 2; i++) { float t; asm volatile("mov.b32 %0, %1;" : "=f"(t) : "f"(acc[i]) : "memory"); acc[i] = t; }
}
template <int G>
__device__ __forceinline__ void conv_pack(const float* X, const float* Y, uint32_t (&r)[4]) {
#pragma unroll
  for (int m = 0; m < 4; m++) {
    const int i = 4 * G + 2 * m;
    r[m] = G < 14 ? pack_bf16(X[i] + Y[i], X[i + 1] + Y[i + 1]) : pack_bf16(X[i], X[i + 1]);
    asm volatile("" : "+r"(r[m]) :: "memory");
  }
}
template <int G>
__device__ __forceinline__ void conv_dump(const float* X, const float* Y, uint32_t pw) {
  uint32_t r[4];
  conv_pack<G>(X, Y, r);
  stmatrix_x4_trans(pw - 256 * G, r[0], r[1], r[2], r[3]);
}
__device__ __forceinline__ void conv_channel(uint32_t hp, uint32_t desc, uint32_t pw, uint32_t tb) {
  float X[64], Y[56];
  uint32_t fx[16], fy[16], f2[16], f3[16], r14[4], r12[4];
  frag_load(fx, hp, 0);
  frag_load(fy, hp, 1);
  conv_issue<0>(X, fx, desc, hp);
  conv_issue<1>(Y, fy, desc, hp);
  frag_load(f2, hp, 2);
  wg_wait<1>(); conv_rename<128>(X); conv_issue<2>(X, f2, desc, hp);
  conv_pack<14>(X, Y, r14);
  frag_load(fx, hp, 3);
  wg_wait<1>(); conv_rename<112>(Y); conv_issue<3>(Y, fx, desc, hp);
  conv_pack<12>(X, Y, r12);
  frag_load(fy, hp, 4);
  wg_wait<1>(); conv_rename<96>(X); conv_issue<4>(X, fy, desc, hp);
  if (JB == 4 && tb) mbar_arrive(tb);
  frag_load(f2, hp, 5);
  bar_sync<NB_PFREE, 224>();
  stmatrix_x4_trans(pw - 256 * 14, r14[0], r14[1], r14[2], r14[3]);
  stmatrix_x4_trans(pw - 256 * 12, r12[0], r12[1], r12[2], r12[3]);
  conv_dump<10>(X, Y, pw);
  frag_load(f3, hp, 6);
  wg_wait<1>(); conv_rename<80>(Y); conv_issue<5>(Y, f2, desc, hp);
  if (JB == 5 && tb) mbar_arrive(tb);
  frag_load(fx, hp, 7);
  conv_dump<8>(X, Y, pw);
  wg_wait<1>(); conv_rename<64>(X); conv_issue<6>(X, f3, desc, hp);
  if (JB == 6 && tb) mbar_arrive(tb);
  conv_dump<6>(X, Y, pw);
  wg_wait<1>(); conv_rename<48>(Y); conv_issue<7>(Y, fx, desc, hp);
  if (JB == 7 && tb) mbar_arrive(tb);
  conv_dump<4>(X, Y, pw);
  wg_wait<1>(); conv_rename<32>(X);
  conv_dump<2>(X, Y, pw);
  wg_wait<0>(); conv_rename<16>(Y);
  conv_dump<0>(X, Y, pw);
}

#define KERNEL_END() do { cluster_arrive(); cluster_wait(); } while (0)

struct Params {
  const __nv_bfloat16 *hr, *hi, *shift_k, *ssm_k, *q, *ssm_D;
  __nv_bfloat16* out;
};

template <int NG>
__device__ __forceinline__ void fin_core(const CUtensorMap* mO, uint32_t qb, uint32_t zb, int tk, int cg, int lane, bool leader, int i, uint32_t bars) {
  const int r = lane & 7, m = lane >> 3;
  const uint32_t qa = qb + r * 64 + ((m ^ (r >> 1)) << 4);
  const uint32_t za = zb + lane * 128 + ((7 ^ r ^ ((tk & 1) ^ 1)) << 4);
  #pragma unroll 1
  for (int h = 0; h < 8; h += NG) {
  uint32_t q[4 * NG], z[4 * NG];
#pragma unroll
  for (int g = 0; g < NG; g++) {
    asm volatile("ldmatrix.sync.aligned.m8n8.x4.shared.b16 {%0,%1,%2,%3}, [%4];" : "=r"(q[4 * g]), "=r"(q[4 * g + 1]), "=r"(q[4 * g + 2]), "=r"(q[4 * g + 3]) : "r"(qa + (h + g) * 512) : "memory");
    asm volatile("ldmatrix.sync.aligned.m8n8.x4.trans.shared.b16 {%0,%1,%2,%3}, [%4];" : "=r"(z[4 * g]), "=r"(z[4 * g + 1]), "=r"(z[4 * g + 2]), "=r"(z[4 * g + 3]) : "r"(za ^ ((h + g) << 4)) : "memory");
  }
#pragma unroll
  for (int g = 0; g < NG; g++)
    stmatrix_x4(qa + (h + g) * 512, bmul2(q[4 * g], z[4 * g]), bmul2(q[4 * g + 1], z[4 * g + 1]), bmul2(q[4 * g + 2], z[4 * g + 2]), bmul2(q[4 * g + 3], z[4 * g + 3]));
  }
  fence_async_smem();
  __syncwarp();
  if (leader) {
    if (i >= 3) STAMP(50 + i);
    asm volatile("cp.async.bulk.tensor.3d.global.shared::cta.tile.bulk_group [%0, {%1, %2, %3}], [%4];"
                 ::"l"((uint64_t)mO), "r"(0), "r"(tk * 64), "r"(20 + cg), "r"(qb) : "memory");
    bulk_commit();
    bulk_wait_read();
    if (i == 3) STAMP(21);
    if (i == 4) STAMP(22);
  }
  __syncwarp();
}

__device__ __forceinline__ void fin_phase(const CUtensorMap* mT, const CUtensorMap* mQ, const CUtensorMap* mO, uint32_t base, uint32_t bars,
                                          int i, int lane, int cta, bool leader) {
  const uint32_t qb = base + q_off(i), zb = base + OFF_PART + (i < 4 ? i * 4096 : 41984);
  const int tk = cta >> 2, cg = (cta & 3) + 4 * i;
  if (leader) {
    const unsigned target = (lds32(EPOCH_WORD) + 1) * 32;
    if (i == 0) STAMP(44);
    if (i == 4) {
      unsigned done = 0;
      auto ok = [&](const uint4& v) {
        const unsigned now = ((int)(v.x - target) >= 0) | ((int)(v.y - target) >= 0) << 1 | ((int)(v.z - target) >= 0) << 2;
        if (now & ~done & 1) mbar_arrive(BAR_EPOCH);
        if (now & ~done & 2) mbar_arrive(BAR_TH);
        done |= now;
        return done == 7;
      };
#pragma unroll 1
      for (int tries = 0; tries < (1 << 17) && !ok(ld_poll(&g_cnt[(16 + (cta & 3)) * 32])); tries++) {}
    } else {
      mbar_wait(i == 3 ? BAR_TH : BAR_EPOCH, i != 3);
    }
    if (i == 4) STAMP(43);
    if (i == 3) STAMP(50);
    fence_async_all();
    tma_load_2d(zb, mT, (31 - tk) * 64, 640 + cg * 32, BAR_U(i));
  }
  __syncwarp();
  mbar_wait(BAR_U(i), 1);
  if (leader && i >= 3) STAMP(48 + i);
  fin_core<8>(mO, qb, zb, tk, cg, lane, leader, i, bars);
}

template <int NT>
__device__ __forceinline__ void z_reduce(uint32_t part, uint32_t img, int wt, uint32_t dd) {
  constexpr int NK = (255 + NT) / NT;
  const uint32_t s0 = part + ((wt ^ ((wt >> 3) & 1)) << 4);
  const uint32_t uo = img + (((255 - wt) ^ (((255 - wt) >> 3) & 1)) << 4);
  const bool last = NK * NT == 256 || wt < 256 - (NK - 1) * NT;
  uint32_t y[NK][4] = {};
#pragma unroll
  for (int k = 0; k < NK; k++) {
    if (k < NK - 1 || last) {
      uint4 v[4] = {};
#pragma unroll
      for (int b = 0; b < 4; b++)
        if (k || wt >= 8 * b) v[b] = lds128((s0 ^ (b & 1) * 16) + k * NT * 16 + b * (4096 - 128));
      y[k][0] = badd2(badd2(v[0].x, v[1].x), badd2(v[2].x, v[3].x)); y[k][1] = badd2(badd2(v[0].y, v[1].y), badd2(v[2].y, v[3].y));
      y[k][2] = badd2(badd2(v[0].z, v[1].z), badd2(v[2].z, v[3].z)); y[k][3] = badd2(badd2(v[0].w, v[1].w), badd2(v[2].w, v[3].w));
    }
  }
  if (NT == 96) bar_arrive<NB_PFREE, 224>();
#pragma unroll
  for (int k = 0; k < NK; k++) {
    if (k < NK - 1 || last) {
      const uint32_t ua = uo - k * NT * 16;
      const uint4 u = lds128(ua);
      sts128(ua, make_uint4(badd2(y[k][0], bmul2(__byte_perm(u.w, 0, 0x1032), dd)), badd2(y[k][1], bmul2(__byte_perm(u.z, 0, 0x1032), dd)),
                            badd2(y[k][2], bmul2(__byte_perm(u.y, 0, 0x1032), dd)), badd2(y[k][3], bmul2(__byte_perm(u.x, 0, 0x1032), dd))));
    }
  }
  fence_async_smem();
}

__device__ __forceinline__ void ldsm_t(uint32_t* r, uint32_t a) {
  asm volatile("ldmatrix.sync.aligned.m8n8.x4.trans.shared.b16 {%0,%1,%2,%3}, [%4];" : "=r"(r[0]), "=r"(r[1]), "=r"(r[2]), "=r"(r[3]) : "r"(a) : "memory");
}
__device__ __forceinline__ void pre_pass(uint32_t base, int lane, int h, int cta, int i) {
  const uint32_t lo = (7 - 2 * (lane >> 3) - (lane & 1)) * 64 + (lane & 6) * 8;
  const uint32_t ks = base + ks_off(i), ak = ks + h * 1024 + lo, tp = base + tap_off(i);
  uint32_t sx, sy, k[12], v[8];
  asm volatile("ld.shared.v2.u32 {%0,%1}, [%2];" : "=r"(sx), "=r"(sy) : "r"(tp + (lane & 3) * 64 + (lane >> 2) * 8) : "memory");
  ldsm_t(k, ak + 512); ldsm_t(k + 4, ak); ldsm_t(k + 8, h ? ak - 512 : tp + (lo | 256));
  ldsm_t(v, ak + 4608); ldsm_t(v + 4, ak + 4096);
  const uint32_t w0 = __byte_perm(sx, 0, 0x1010), w1 = __byte_perm(sx, 0, 0x3232), w2 = __byte_perm(sy, 0, 0x1010), w3 = __byte_perm(sy, 0, 0x3232);
  uint32_t s1 = __byte_perm(k[0], k[1], 0x5432);
#pragma unroll
  for (int j = 0; j < 8; j++) {
    const uint32_t s3 = __byte_perm(k[j + 1], k[j + 2], 0x5432);
    uint32_t a = bmul2(s3, w3);
    a = badd2(a, bmul2(k[j + 1], w2));
    a = badd2(a, bmul2(s1, w1));
    a = badd2(a, bmul2(k[j], w0));
    v[j] = bmul2(a, v[j]);
    s1 = s3;
  }
  bar_sync<NB_PRE, 128>();
  const uint32_t o0 = ks + 4096 + lane * 128 + (((2 * h ^ 7 ^ (cta >> 2 & 1) ^ lane) & 7) << 4);
  sts128(o0, make_uint4(v[0], v[1], v[2], v[3]));
  sts128(o0 ^ 16, make_uint4(v[4], v[5], v[6], v[7]));
  fence_async_smem();
}

__global__ void __cluster_dims__(2, 1, 1) __launch_bounds__(NTHREADS, 1)
fused_kernel(const __grid_constant__ Params p, const __grid_constant__ CUtensorMap mX, const __grid_constant__ CUtensorMap mHr, const __grid_constant__ CUtensorMap mHi,
             const __grid_constant__ CUtensorMap mCr, const __grid_constant__ CUtensorMap mCi,
             const __grid_constant__ CUtensorMap mT, const __grid_constant__ CUtensorMap mS, const __grid_constant__ CUtensorMap mKh,
             const __grid_constant__ CUtensorMap mK, const __grid_constant__ CUtensorMap mV,
             const __grid_constant__ CUtensorMap mQ, const __grid_constant__ CUtensorMap mO) {
  extern __shared__ __align__(1024) unsigned char smem_raw[];
  const uint32_t base = smem_u32(smem_raw);
  const uint32_t bars = base + OFF_BAR;
  const int tid = threadIdx.x;
  const int cta = blockIdx.x, cid = blockIdx.x >> 1;
  const uint32_t rank = cta & 1;
  const CUtensorMap* mC = rank ? &mCi : &mCr;
  int tb, db;
  {
    const int t = cid - 4, q7 = ((t - 32) * 37) >> 8;
    int v = t < 32 ? (t & 7) * 8 + (t >> 3) : (t - 31 - 7 * q7) * 8 + 4 + q7;
    v = t < 0 ? 4 + cid : v;
    tb = v >> 2; db = v & 3;
  }
  if (tid >= 480 && elect_one()) {
#pragma unroll 1
    for (int it = 0; it < XOWN; it++) {
      const uint32_t sa = base + it * STAGE_BYTES, bf = BAR_FULL(it);
      mbar_init(bf, 1);
      asm volatile("fence.mbarrier_init.release.cluster;" ::: "memory");
      mbar_expect_tx(bf, STAGE_BYTES);
      tma_load_2d(sa, mC, it * 64, tb * 128, bf);
      tma_load_3d(sa + A_BYTES, &mX, 0, it * 64, db * 5, bf);
      tma_load_3d(sa + A_BYTES + 10240, &mX, 0, it * 64 + 32, db * 5, bf);
      if (it == 0) VAL(58, clock64() - c_entry);
    }
    VAL(62, clock64() - c_entry);
  }
  const int warp = __shfl_sync(0xffffffffu, tid >> 5, 0), lane = tid & 31;
  const int wgi = warp >> 2, w = warp & 3, wt = tid & 127;
  const int odd = db & 1;
  const bool leader = elect_one();
  if (leader && warp < 15) {
#pragma unroll 1
    for (int b = XOWN + 2 * warp; b < min(XOWN + 2 + 2 * warp, 31); b++) {
      mbar_init(bars + 8 * b, (b >= 5 && b < 10) ? 4 : (b >= 22 && b < 28 ? 2 : 1));
      if (b >= 10 && b < 22) mbar_expect_tx(bars + 8 * b, b >= 17 ? 4096 : (b >= 15 ? 10240 : 8192 + 512));
    }
    asm volatile("fence.mbarrier_init.release.cluster;" ::: "memory");
  }
  __syncwarp();
  cluster_arrive();
  if (warp < 15) cluster_wait();
  if (wgi == 3) {
    reg_dec<R_AUX>();
    auto kv_load = [&](int e) {
      const int i = e >> 1, cg = (cta & 3) + 4 * i;
      tma_load_3d(base + ks_off(i) + (e & 1) * 4096, (e & 1) ? &mV : &mK, 0, (cta >> 2) * 64, cg, BAR_KV(i));
      if (e & 1) bulk_load(base + tap_off(i), p.shift_k + cg * 128, 256, BAR_KV(i));
      else tma_load_3d(base + tap_off(i) + 256, &mKh, 0, (cta >> 2) * 64 - 4, cg, BAR_KV(i));
    };
    if (warp == 15) {
      if (leader) { VAL(57, clock64() - c_entry); STAMPC(30); VAL(55, smid()); VAL(56, tb * 4 + db); }
      int s = XOWN % STAGES, ph = XOWN < STAGES;
      cluster_wait();
      if (leader) VAL(59, clock64() - c_entry);
#pragma unroll 1
      for (int it = XOWN; it < 32; it++) {
        const uint32_t sa = base + s * STAGE_BYTES, bf = BAR_FULL(s);
        if (it >= STAGES) mbar_wait(BAR_EMPTY(s), ph);
        if (leader) {
          mbar_expect_tx(bf, STAGE_BYTES);
          tma_load_2d(sa, mC, it * 64, tb * 128, bf);
          tma_load_3d_mc(sa + A_BYTES + rank * 10240, &mX, 0, it * 64 + rank * 32, db * 5, bf, 3);
          const unsigned e = it - G_KV;
          if (e < 6) kv_load(e);
          if ((unsigned)(it - G_T) < 4) bulk_prefetch(p.ssm_k + (size_t)(cta + 128 * (it - G_T + 1)) * 2048, 4096);
          if ((unsigned)(it - G_Q) < 2) bulk_prefetch(p.q + (size_t)(cta * 2 + it - G_Q) * 8 * 640, 8 * 1280);
          if (it == G_H) bulk_prefetch((rank ? p.hi : p.hr) + (size_t)cid * 10 * 640, 10 * 1280);
        }
        if (++s == STAGES) { s = 0; ph ^= 1; }
      }
      if (leader) {
        const CUtensorMap* mH = rank ? &mHi : &mHr;
        const int kb5 = (db >> 1) * 5;
        unsigned char* ub = g_u + (size_t)(tb * 2 + rank) * 10 * A_BYTES;
        unsigned* flags = g_flag + (tb * 2 + rank) * 32;
        unsigned tag = 0, seen = 0;
        mbar_wait(BAR_EPOCH, 0);
        tag = (lds32(EPOCH_WORD) + 1) * 6;
#pragma unroll 1
        for (int i = 7 - NBE; i < 15; i++) {
          const int j = i < 7 ? i - (7 - NBE) : i - 5;
          const bool doA = i >= 7, doB = i < 7 || j >= NBE;
          const int kb = (j < 5) ? kb5 + (odd ? (j < 2 ? j + 3 : (j == 2 ? 2 : j - 3)) : j) : j - kb5;
          s = (32 + j) % STAGES;
          const uint32_t sa = base + s * STAGE_BYTES, bf = BAR_FULL(s);
          if (doA) {
            const unsigned need = ALLF == 1 || (ALLF == 2 && j > 2) ? 15 : j < 5 ? 1u << (db ^ 1) : (j < 7 ? 15 - (2 << ((db ^ 2) & 2)) : 15);
            if ((seen & need) != need) {
#pragma unroll 1
              for (int tries = 0; tries < (1 << 18); tries++) {
                uint4 f;
                asm volatile("ld.acquire.gpu.global.v4.u32 {%0,%1,%2,%3}, [%4];" : "=r"(f.x), "=r"(f.y), "=r"(f.z), "=r"(f.w) : "l"(flags) : "memory");
                seen = (f.x == tag) | (f.y == tag) << 1 | (f.z == tag) << 2 | (f.w == tag) << 3;
                if ((seen & need) == need) break;
              }
              fence_async_all();
            }
            if (j == 2) STAMP(4);
            if (i == 12) STAMP(5);
          }
          if (doB) {
            mbar_wait(BAR_EMPTY(s), ((32 + j) / STAGES & 1) ^ 1);
            if (EF && j == 3) {
#pragma unroll 1
              for (int e = 0; e < 2; e++) {
                mbar_expect_tx(BAR_KV(2 + e), 8192);
                tma_load_3d(sa + e * 8192, &mQ, 0, (cta >> 2) * 64, (cta & 3) + 4 * e, BAR_KV(2 + e));
                tma_load_2d(sa + e * 8192 + 4096, &mT, (31 - (cta >> 2)) * 64, 640 + ((cta & 3) + 4 * e) * 32, BAR_KV(2 + e));
              }
            }
            mbar_expect_tx(bf, B_BYTES + (j < 2 ? 0 : (j == 2 ? 8192 : A_BYTES)));
            tma_load_5d(sa + A_BYTES, mH, kb * 64, db * 10 + rank * 5, bf);
            tma_load_5d(sa + A_BYTES + 10240, mH, kb * 64, db * 10 + (rank ^ 1) * 5, bf);
            if (EF && j == EFP) { wait_ge(&g_cnt[(16 + (cta & 3)) * 32 + 3], (lds32(EPOCH_WORD) + 1) * 32); fence_async_all(); }
          }
          if (doA) {
            if (EF && j == 3) { mbar_wait(BAR_KV(0), 1); mbar_wait(BAR_KV(1), 1); }
            const uint32_t off = j == 2 ? (odd ^ 1) * 4096 : 0, sz = j == 2 ? 4096 : 8192;
            bulk_load(sa + off, ub + kb * A_BYTES + off, sz, bf);
            bulk_load(sa + off + 8192, ub + kb * A_BYTES + off + 8192, sz, bf);
          }
        }
      }
      __syncwarp();
    } else {
      unsigned target = 0;
      if (w == 1 && leader) {
        target = atomicAdd(&g_ticket, 1u) / NCTA;
        asm volatile("st.shared.u32 [%0], %1;" ::"r"(EPOCH_WORD), "r"(target) : "memory");
        mbar_arrive(BAR_EPOCH);
        target = (target + 1) * 32;
      }
      const int tu = lane + w * 16;
      const __nv_bfloat16* hsrc = p.ssm_k + (size_t)cta * 2048 + tu * 8;
      asm volatile("st.shared.v2.u32 [%0], {%1, %1};" ::"r"(base + OFF_UB + w * U_BYTES + 4096 + lane * 8), "r"(0) : "memory");
      fence_async_smem();
      mbar_wait_slow(BAR_KV(0), 0);
      const uint32_t dall = (uint32_t)__bfloat16_as_ushort(p.ssm_D[cta + 128 * min(lane, 4)]);
#pragma unroll 1
      for (int st = 0; st < 7; st++) {
        const int hs = st < 4 ? st - 2 : (st == 4 ? -1 : st - 3);
        const bool tab = st < 6 && st != 1 && w != 1;
        uint4 hv[4] = {}, hw[4] = {};
        if (tab) {
          uint32_t hpv[4] = {};
#pragma unroll
          for (int i = 0; i < 4; i++) {
            hv[i] = ldg128(hsrc + i * 512);
            if (lane == 0 && (i || wt)) hpv[i] = ldg32(hsrc + i * 512 - 2);
          }
          hsrc += 128 * 2048;
#pragma unroll
          for (int i = 0; i < 4; i++) {
            const uint32_t up = __shfl_up_sync(0xffffffffu, hv[i].w, 1);
            if (lane) hpv[i] = up;
            hw[i] = make_uint4(__byte_perm(hpv[i], hv[i].x, 0x5432), __byte_perm(hv[i].x, hv[i].y, 0x5432),
                               __byte_perm(hv[i].y, hv[i].z, 0x5432), __byte_perm(hv[i].z, hv[i].w, 0x5432));
            asm volatile("" : "+r"(hw[i].x), "+r"(hw[i].y), "+r"(hw[i].z), "+r"(hw[i].w));
          }
        }
        if (st & 3) bar_sync<NB_PFULL, 224>();
        auto tab_store = [&]() {
          if (st == 4) bar_sync<NB_T0, 96>();
          const uint32_t a = base + OFF_HT + (st != 4) * HT_BYTES + 32 + tu * 16;
          if (wt < 4) sts128(a - 32 + (wt >> 1) * (HC_BYTES - 32), make_uint4(0, 0, 0, 0));
#pragma unroll
          for (int i = 0; i < 4; i++) {
            sts128(a + i * 1024, hv[i]);
            sts128(a + i * 1024 + HC_BYTES, hw[i]);
          }
          __syncwarp();
          if (leader) mbar_arrive(BAR_TAB(max(st - 1, 0)));
        };
        if (tab && (!RFIRST || st != 5)) tab_store();
        if (hs >= 0) {
          const uint32_t dd = __shfl_sync(0xffffffffu, dall, hs) * 0x10001u;
          if (wt == 4) asm volatile("st.shared.u32 [%0], %1;" ::"r"(EPOCH_WORD + 4), "r"(dall * 0x10001u) : "memory");
          z_reduce<96>(base + OFF_PART, base + u_off(hs), wt, dd);
          bar_sync<NB_AUX, 96>();
        }
        if (RFIRST && tab && st == 5) tab_store();
        if (w == 1 && st != 4) {
          const int f = st < 2 ? st : st + 1, l = st < 4 ? (st == 1 ? 3 : f + 1) : 0;
          if (st < 4 && st != 1) bar_sync<NB_PUB, 160>();
          if (leader) {
            if (st < 3) STAMP(st == 0 ? 33 : 47);
#pragma unroll 1
            for (int i = f; i < l; i++)
              asm volatile("cp.async.bulk.tensor.4d.global.shared::cta.tile.bulk_group [%0, {%1, %2, %2, %3}], [%4];"
                           ::"l"((uint64_t)&mS), "r"((31 - (cta >> 2)) * 64), "r"(0), "r"((cta & 3) + 4 * i), "r"(base + ks_off(i) + 4096) : "memory");
            if (hs >= 0) bulk_store(g_t + (size_t)(640 + cta + 128 * hs) * 4096, base + u_off(hs), 4096);
            bulk_commit();
            bulk_wait_all();
            red_relaxed_add(&g_cnt[st < 4 ? (4 * st + (cta & 3)) * 32 : (16 + (cta >> 5)) * 32 + st - 5], 1u);
            if (st < 3) STAMP(st == 0 ? 34 : 48);
            if (EF && st == 3) red_relaxed_add(&g_cnt[(16 + (cta >> 5)) * 32 + 3], 1u);
            if ((unsigned)(st - 1) < 2) {
              if (st == 1) mbar_wait_slow(BAR_U(0), 0);
              kv_load(2 * st + 4); kv_load(2 * st + 5);
            }
          }
          __syncwarp();
          if (st == 3) bar_arrive<NB_T0, 96>();
        }
        if (st == 1) bar_arrive<NB_PFREE, 224>();
        if (EF && st == 5 && w != 1) {
          const uint32_t sa = base + (35 % STAGES) * STAGE_BYTES + w * 4096;
          if (leader && w == 2) STAMP(48);
          mbar_wait(BAR_KV(2 + (w >> 1)), 1);
          if (leader && w == 2) STAMP(49);
          fin_core<4>(&mO, sa, sa + 4096, cta >> 2, (cta & 3) + 2 * w, lane, leader, 0, bars);
          if (leader) mbar_arrive(BAR_KV(w >> 1));
          if (leader && w == 2) STAMP(47);
        }
        if (w == 1 && leader) {
          if (hs >= 3) {
#pragma unroll 1
            for (int i = EF ? 2 : 0; i < 3; i++) {
              mbar_expect_tx(BAR_U(i), 8192);
              tma_load_3d(base + q_off(i), &mQ, 0, (cta >> 2) * 64, (cta & 3) + 4 * i, BAR_U(i));
            }
          }
          if (st < 4) {
            wait_ge(&g_cnt[(4 * st + (cta >> 5)) * 32], target);
            if (st < 3) STAMP(st == 0 ? 35 : 49);
            fence_async_all();
#pragma unroll 1
            for (int c = st < 2 ? st : st + 1; c < (st ? st + 2 : 1); c++) bulk_load(base + u_off(c), g_t + (size_t)(cta + 128 * c) * 4096, 4096, BAR_U(c));
          }
        }
        __syncwarp();
      }
      __syncwarp();
    }
  } else if (wgi == 0) {
    reg_inc<R_CONV>();
    const int x00 = 64 * w + (lane >> 2) + 2 * (lane & 3) + 1;
    const uint32_t hp = base + OFF_HT + ((x00 & 1) ? HC_BYTES + 2 * (x00 + 1) : 2 * x00);
    const int cn = 254 - (lane & 16) - 2 * (lane & 7) + ((lane >> 3) & 1);
    const uint32_t pw = base + OFF_PART + w * 4096 + ((cn ^ ((cn >> 3) & 1)) << 4);
#pragma unroll 1
    for (int c = 0, i = 0; c < 5; c++) {
#pragma unroll 1
      for (; i < min(c + 3, 5); i++) {
        mbar_wait_slow(BAR_KV(i), 0);
        if (wt == 0 && i == 0) STAMP(32);
        if (wt == 0 && i == 2) STAMP(46);
        pre_pass(base, lane, w, cta, i);
        if (i == 2) bar_arrive<NB_PFULL, 224>();
        else if (i != 1) bar_arrive<NB_PUB, 160>();
        if (wt == 0 && i == 2) STAMP(45);
        if (wt == 0 && i == 3) STAMP(61);
      }
      mbar_wait_slow(BAR_U(c), 0);
      mbar_wait(BAR_TAB(c), 0);
      if (wt == 0) { STAMP(10 + 2 * c); ITC(128 + 2 * c); }
      conv_channel(hp + (c != 3) * HT_BYTES, (uint32_t)mkdesc(base + u_off(c), 16, 256, 3), pw,
                   0);
      if (wt == 0) { STAMP(11 + 2 * c); ITC(129 + 2 * c); }
      if (c < 4) bar_arrive<NB_PFULL, 224>();
    }
    if (wt == 0) mbar_arrive(BAR_CDONE);
    bar_sync<NB_PRE, 128>();
    z_reduce<128>(base + OFF_PART, base + u_off(4), wt, lds32(EPOCH_WORD + 4));
    bar_sync<NB_PRE, 128>();
    if (warp == 3 && leader) {
      STAMP(20);
      bulk_store(g_t + (size_t)(640 + cta + 512) * 4096, base + u_off(4), 4096);
      bulk_commit();
      mbar_expect_tx(BAR_U(3), 8192);
      tma_load_3d(base + q_off(3), &mQ, 0, (cta >> 2) * 64, (cta & 3) + 12, BAR_U(3));
      bulk_wait_all();
      red_relaxed_add(&g_cnt[(16 + (cta >> 5)) * 32 + 2], 1u);
      STAMP(42);
      mbar_expect_tx(BAR_U(4), 8192);
      tma_load_3d(base + q_off(4), &mQ, 0, (cta >> 2) * 64, (cta & 3) + 16, BAR_U(4));
    }
    __syncwarp();
  } else {
    reg_dec<R_GEMM>();
    const int wg = wgi - 1;
    float acc[80];
    int s = 0, ph = 0;
#pragma unroll 1
    for (int it = 0; it < 32; it++) {
      mbar_wait(BAR_FULL(s), ph);
      const uint32_t sa = base + s * STAGE_BYTES + wg * 8192, sb = base + s * STAGE_BYTES + A_BYTES;
      const uint64_t da = mkdesc(sa, 16, 1024, 1), db_ = mkdesc(sb, 2048, 512, 2);
#pragma unroll
      for (int i = 0; i < 80; i++) asm volatile("" : "+f"(acc[i])::"memory");
      wg_fence();
      wgmma_ss_tb160(acc, da, db_, it != 0);
      wgmma_ss_tb160(acc, da + 2, db_ + 64, 1);
      wgmma_ss_tb160(acc, da + 4, db_ + 640, 1);
      wgmma_ss_tb160(acc, da + 6, db_ + 704, 1);
      wg_commit();
      wg_wait<0>();
      if (wt < 2) mbar_arrive_cta(BAR_EMPTY(s), wt);
      if (++s == STAGES) { s = 0; ph ^= 1; }
    }
#pragma unroll
    for (int i = 0; i < 80; i++) asm volatile("" : "+f"(acc[i])::"memory");
    if (wt == 0) STAMP(wg ? 38 : 2);
    if (wt == 0) ITC(wg * 64 + 42);
    const int m = lane >> 3, i8 = lane & 7;
    {
      const int row = 16 * w + 8 * (m & 1) + i8;
      const uint32_t ad0 = base + (32 % STAGES) * STAGE_BYTES + wg * 8192 + row * 64 + (((m >> 1) ^ ((row >> 1) & 3)) << 4);
#pragma unroll
      for (int lc = 0; lc < 5; lc++) {
        const int e0 = lc, e1 = lc == 0 ? 5 : lc - 1;
        const uint32_t ad = ad0 + (odd ? (e1 >> 1) * STAGE_BYTES + (e1 & 1) * 4096 : (e0 >> 1) * STAGE_BYTES + (e0 & 1) * 4096);
#pragma unroll
        for (int h = 0; h < 2; h++) {
          const int G = lc * 4 + h * 2;
          stmatrix_x4(ad ^ (h * 32), pack_bf16(acc[4 * G], acc[4 * G + 1]), pack_bf16(acc[4 * G + 2], acc[4 * G + 3]),
                      pack_bf16(acc[4 * G + 4], acc[4 * G + 5]), pack_bf16(acc[4 * G + 6], acc[4 * G + 7]));
        }
      }
      if (leader && warp == 4) STAMP(36);
      fence_async_smem();
      asm volatile("bar.sync %0, 128;" ::"r"(NB_G0 + wg) : "memory");
      if (leader && warp == 4) STAMP(37);
      if (leader && w < 3) {
        const uint32_t off = wg * 8192 + (w == 2 ? odd * 4096 : 0);
        bulk_store(g_u + (size_t)((tb * 2 + rank) * 10 + (db >> 1) * 5 + (odd && w < 2 ? w + 3 : w)) * A_BYTES + off,
                   base + (32 % STAGES + w) * STAGE_BYTES + off, w == 2 ? 4096 : 8192);
        bulk_commit();
        if (warp == 4) STAMP(23);
      }
      __syncwarp();
    }
#pragma unroll 1
    for (int it = 32; it < 42; it++) {
      if (it == 32 + CPRI) mbar_wait(BAR_CDONE, 0);
      mbar_wait(BAR_FULL(s), ph);
      const uint32_t sa = base + s * STAGE_BYTES + wg * 8192, sb = base + s * STAGE_BYTES + A_BYTES;
      const uint64_t da = mkdesc(sa, 16, 512, 2), db_ = mkdesc(sb, 16, 1024, 1);
#pragma unroll
      for (int i = 0; i < 80; i++) asm volatile("" : "+f"(acc[i])::"memory");
      wg_fence();
      wgmma_ss<160>(acc, da, db_, it != 32);
      wgmma_ss<160>(acc, da + 2, db_ + 2, 1);
      wgmma_ss<160>(acc, da + 256, db_ + 4, 1);
      wgmma_ss<160>(acc, da + 258, db_ + 6, 1);
      wg_commit();
      if (it == 31 + WPUB && leader && w < 3) {
        bulk_wait_all();
        red_relaxed_add(g_flag + (tb * 2 + rank) * 32 + db, 1u);
        if (warp == 4) STAMP(3);
      }
      __syncwarp();
      wg_wait<0>();
      if (wt < 2) mbar_arrive(BAR_EMPTY(s));
      if (it == 42 - STAGES && wt == 0) mbar_arrive_cta(BAR_XFREE, rank ^ 1);
      if (++s == STAGES) { s = 0; ph ^= 1; }
    }
#pragma unroll
    for (int i = 0; i < 80; i++) asm volatile("" : "+f"(acc[i])::"memory");
    if (wt == 0) STAMP(wg ? 41 : 6);
    if (wt == 0) ITC(wg * 64 + 43);
    {
      const uint32_t xw = base + ((42 - STAGES) % STAGES) * STAGE_BYTES + wg * 10240 + w * 2560, xb = xw + lane * 16;
      const uint32_t rxb = mapa(xb, rank ^ 1), rbar = mapa(BAR_XFULL(wg), rank ^ 1);
      CS(57);
      mbar_wait(BAR_XFREE, 0);
#pragma unroll
      for (int i = 0; i < 5; i++)
        st_async128(rxb + i * 512, make_uint4(pack_bf16(acc[40 + 8 * i], acc[40 + 8 * i + 1]), pack_bf16(acc[40 + 8 * i + 2], acc[40 + 8 * i + 3]),
                                              pack_bf16(acc[40 + 8 * i + 4], acc[40 + 8 * i + 5]), pack_bf16(acc[40 + 8 * i + 6], acc[40 + 8 * i + 7])), rbar);
      if (wg == 0 && wt == 0) STAMP(40);
      uint32_t own[20];
#pragma unroll
      for (int i = 0; i < 20; i++) {
        own[i] = pack_bf16(acc[2 * i], acc[2 * i + 1]) ^ (rank * 0x80008000u);
        asm volatile("" : "+r"(own[i]) :: "memory");
      }
      const uint32_t sr = rank ? 0x3f803f80u : 0xbf80bf80u;
      __nv_bfloat16* op = p.out + (size_t)(tb * 128 + wg * 64 + w * 16 + (lane >> 2)) * 1280 + db * 160 + rank * 80 + (lane & 3) * 4;
      asm volatile("" : "+l"(op) :: "memory");
      CS(58);
      mbar_wait(BAR_XFULL(wg), 0);
      CS(59);
      if (wg == 0 && wt == 0) STAMP(28);
      uint4 r[5];
#pragma unroll
      for (int i = 0; i < 5; i++) r[i] = lds128(xb + i * 512);
      __syncwarp();
      auto comb = [&](int i, uint32_t v) { uint32_t d; asm("fma.rn.bf16x2 %0, %1, %2, %3;" : "=r"(d) : "r"(v), "r"(sr), "r"(own[i])); return d; };
#pragma unroll
      for (int i = 0; i < 5; i++) {
        *(uint2*)(op + 16 * i) = make_uint2(comb(4 * i, r[i].x), comb(4 * i + 2, r[i].z));
        *(uint2*)(op + 16 * i + 8 * 1280) = make_uint2(comb(4 * i + 1, r[i].y), comb(4 * i + 3, r[i].w));
      }
      CS(60);
      CS(63);
      if (wt == 0) STAMP(wg ? 7 : 60);
      if (wg == 0 && wt == 0) { STAMPC(31); ITC(44); }
    }
  }
  if ((warp < 4 && warp >= 2 * EF) || warp == 13) fin_phase(&mT, &mQ, &mO, base, bars, min(warp, 4), lane, cta, leader);
  KERNEL_END();
}

typedef CUresult (*PFN_encodeTiled)(CUtensorMap*, CUtensorMapDataType, cuuint32_t, void*, const cuuint64_t*, const cuuint64_t*,
                                    const cuuint32_t*, const cuuint32_t*, CUtensorMapInterleave, CUtensorMapSwizzle,
                                    CUtensorMapL2promotion, CUtensorMapFloatOOBfill);

static CUtensorMap make_map(PFN_encodeTiled enc, const void* ptr, uint64_t inner, uint64_t outer, uint32_t box_inner, uint32_t box_outer,
                            CUtensorMapSwizzle swz, CUtensorMapL2promotion prom = CU_TENSOR_MAP_L2_PROMOTION_L2_128B) {
  CUtensorMap m;
  cuuint64_t dims[2] = {inner, outer};
  cuuint64_t strides[1] = {inner * 2};
  cuuint32_t box[2] = {box_inner, box_outer};
  cuuint32_t es[2] = {1, 1};
  enc(&m, CU_TENSOR_MAP_DATA_TYPE_BFLOAT16, 2, const_cast<void*>(ptr), dims, strides, box, es, CU_TENSOR_MAP_INTERLEAVE_NONE, swz,
      prom, CU_TENSOR_MAP_FLOAT_OOB_FILL_NONE);
  return m;
}

extern "C" void kernel_launch(void* const* d_in, const int* in_sizes, int n_in, void* d_out, int out_size) {
  static PFN_encodeTiled enc = nullptr;
  static void* gt = nullptr;
  if (!enc) {
    cudaGetSymbolAddress(&gt, g_t);
    void* fp = nullptr;
    cudaDriverEntryPointQueryResult qr;
    cudaGetDriverEntryPoint("cuTensorMapEncodeTiled", &fp, cudaEnableDefault, &qr);
    enc = (PFN_encodeTiled)fp;
    cudaFuncSetAttribute(fused_kernel, cudaFuncAttributeMaxDynamicSharedMemorySize, SMEM_BYTES);
  }
  auto map3 = [&](const void* ptr, uint32_t rows, uint32_t groups, CUtensorMapSwizzle swz, int prom, uint64_t w = 1) {
    CUtensorMap m;
    cuuint64_t dims[3] = {32, 2048, 20 * w};
    cuuint64_t strides[2] = {1280 * w, 64};
    cuuint32_t box[3] = {32, rows, groups};
    cuuint32_t es[3] = {1, 1, 1};
    enc(&m, CU_TENSOR_MAP_DATA_TYPE_BFLOAT16, 3, const_cast<void*>(ptr), dims, strides, box, es, CU_TENSOR_MAP_INTERLEAVE_NONE, swz,
        (CUtensorMapL2promotion)prom, CU_TENSOR_MAP_FLOAT_OOB_FILL_NONE);
    return m;
  };
  CUtensorMap mX = map3(d_in[0], 32, 5, CU_TENSOR_MAP_SWIZZLE_64B, 2);
  CUtensorMap mKh = map3(d_in[6], 4, 1, CU_TENSOR_MAP_SWIZZLE_NONE, 2);
  CUtensorMap mK = map3(d_in[6], 64, 1, CU_TENSOR_MAP_SWIZZLE_NONE, 2);
  CUtensorMap mV = map3(d_in[7], 64, 1, CU_TENSOR_MAP_SWIZZLE_NONE, 2);
  CUtensorMap mQ = map3(d_in[5], 64, 1, CU_TENSOR_MAP_SWIZZLE_64B, 2);
  CUtensorMap mO = map3(d_out, 64, 1, CU_TENSOR_MAP_SWIZZLE_64B, 2, 2);
  CUtensorMap mCr = make_map(enc, d_in[1], 2048, 2048, 64, 128, CU_TENSOR_MAP_SWIZZLE_128B, CU_TENSOR_MAP_L2_PROMOTION_L2_128B);
  CUtensorMap mCi = make_map(enc, d_in[2], 2048, 2048, 64, 128, CU_TENSOR_MAP_SWIZZLE_128B, CU_TENSOR_MAP_L2_PROMOTION_L2_128B);
  auto map5 = [&](const void* ptr) {
    CUtensorMap m;
    cuuint64_t dims[5] = {640, 2, 4, 2, 40};
    cuuint64_t strides[4] = {1280, 4 * 1280, 2 * 1280, 16 * 1280};
    cuuint32_t box[5] = {64, 2, 4, 2, 5};
    cuuint32_t es[5] = {1, 1, 1, 1, 1};
    enc(&m, CU_TENSOR_MAP_DATA_TYPE_BFLOAT16, 5, const_cast<void*>(ptr), dims, strides, box, es, CU_TENSOR_MAP_INTERLEAVE_NONE,
        CU_TENSOR_MAP_SWIZZLE_128B, CU_TENSOR_MAP_L2_PROMOTION_L2_128B, CU_TENSOR_MAP_FLOAT_OOB_FILL_NONE);
    return m;
  };
  CUtensorMap mHr = map5(d_in[3]), mHi = map5(d_in[4]);
  CUtensorMap mT = make_map(enc, gt, 2048, 1280, 64, 32, CU_TENSOR_MAP_SWIZZLE_128B);
  CUtensorMap mS;
  {
    cuuint64_t dims[4] = {2048, 4, 8, 20};
    cuuint64_t strides[3] = {8 * 4096, 4096, 32 * 4096};
    cuuint32_t box[4] = {64, 4, 8, 1};
    cuuint32_t es[4] = {1, 1, 1, 1};
    enc(&mS, CU_TENSOR_MAP_DATA_TYPE_BFLOAT16, 4, gt, dims, strides, box, es, CU_TENSOR_MAP_INTERLEAVE_NONE, CU_TENSOR_MAP_SWIZZLE_128B,
        CU_TENSOR_MAP_L2_PROMOTION_L2_128B, CU_TENSOR_MAP_FLOAT_OOB_FILL_NONE);
  }
  Params p;
  p.hr = (const __nv_bfloat16*)d_in[3];
  p.hi = (const __nv_bfloat16*)d_in[4];
  p.q = (const __nv_bfloat16*)d_in[5];
  p.shift_k = (const __nv_bfloat16*)d_in[8];
  p.ssm_k = (const __nv_bfloat16*)d_in[9];
  p.ssm_D = (const __nv_bfloat16*)d_in[10];
  p.out = (__nv_bfloat16*)d_out;
  fused_kernel<<<NCTA, NTHREADS, SMEM_BYTES>>>(p, mX, mHr, mHi, mCr, mCi, mT, mS, mKh, mK, mV, mQ, mO);
}
```
